```python
import torch

def _softmax(x, axis=-1):
    return torch.softmax(x, dim=axis)
def _gelu(x):
    return torch.nn.functional.gelu(x, approximate="tanh")
def _silu(x):
    return torch.nn.functional.silu(x)
def _sigmoid(x):
    return torch.sigmoid(x)
def _layernorm(x, axis=-1, eps=1e-5):
    m = x.mean(dim=axis, keepdim=True)
    v = x.var(dim=axis, keepdim=True, unbiased=False)
    return (x - m) / torch.sqrt(v + eps)
def _scatter_add(tgt, idx, src, axis=0):
    return tgt.clone().index_add_(axis, idx, src)
def _segment_sum(src, seg, n):
    out = torch.zeros((n,) + src.shape[1:], dtype=src.dtype)
    return out.index_add_(0, seg, src)
def _pad(x, pw):
    flat = tuple(v for pair in reversed(pw) for v in pair)
    return torch.nn.functional.pad(x, flat)

kernel_name = 'standalone__normalfloat_lut_codebook_lookup__prompt'

def setup_inputs():

    _w = (lambda a: (lambda t: t.to(torch.bfloat16) if t.is_floating_point() else t)(torch.as_tensor(a)))
    B, S, D, F = 1, 2048, 1024, 3584
    G = 64 if 64 > 0 else D
    D = (D // G) * G
    ng = D // G
    nf4 = torch.tensor([
        -1.0, -0.6961928009986877, -0.5250730514526367, -0.39491748809814453,
        -0.28444138169288635, -0.18477343022823334, -0.09105003625154495, 0.0,
        0.07958029955625534, 0.16093020141124725, 0.24611230194568634, 0.33791524171829224,
        0.44070982933044434, 0.5626170039176941, 0.7229568362236023, 1.0
    ], dtype=float)
    qw = torch.randint(0, 16, (D, F)).to(torch.int64)
    absmax = (torch.abs((lambda *s: torch.randn(*s, dtype=torch.bfloat16) * 0.05)(ng, F)) + 0.01).to(float)
    return {
        "x": _w((lambda *s: torch.randn(*s, dtype=torch.bfloat16) * 0.05)(B, S, D)),
        "qw": _w(qw),
        "codebook": _w(nf4),
        "absmax": _w(absmax),
    }

def reference(x, qw, codebook, absmax):
    B, S, D = x.shape
    ng, F = absmax.shape
    G = D // ng
    w_nf = codebook[qw]
    s = (lambda x, n, axis: torch.repeat_interleave(x, n, dim=axis))(absmax, G, axis=0)
    w = (lambda x, dt: x.to(dt))(w_nf * s, x.dtype)
    return torch.einsum("bsd,df->bsf", x, w)
```

```cpp
#include <cuda_runtime.h>
#include <cuda_bf16.h>
#include <cuda.h>
#include <stdint.h>

constexpr int M_ = 2048, K_ = 1024, N_ = 3584;
constexpr int BM = 256, BN = 224, BK = 64;
constexpr int KC = K_ / BK;

#define TSW(w, i)
#define TS_INIT()
#define TS_DUMP()

#define TC(i)
__device__ __forceinline__ uint32_t smem_u32(const void* p) { return (uint32_t)__cvta_generic_to_shared(p); }
__device__ __forceinline__ bool elect() {
    uint32_t ok;
    asm volatile("{\n.reg .pred p;\nelect.sync _|p, 0xffffffff;\nselp.u32 %0, 1, 0, p;\n}\n" : "=r"(ok));
    return ok != 0;
}
__device__ __forceinline__ void mbar_init(uint32_t bar, uint32_t cnt) { asm volatile("mbarrier.init.shared::cta.b64 [%0], %1;" ::"r"(bar), "r"(cnt) : "memory"); }
__device__ __forceinline__ void mbar_expect_tx(uint32_t bar, uint32_t bytes) { asm volatile("mbarrier.arrive.expect_tx.shared::cta.b64 _, [%0], %1;" ::"r"(bar), "r"(bytes) : "memory"); }
__device__ __forceinline__ void mbar_arrive(uint32_t bar) { asm volatile("mbarrier.arrive.shared::cta.b64 _, [%0];" ::"r"(bar) : "memory"); }
__device__ __forceinline__ void mbar_wait(uint32_t bar, uint32_t parity) {
    asm volatile(
        "{\n.reg .pred p;\n.reg .b32 n;\n"
        "mbarrier.try_wait.parity.shared::cta.b64 p, [%0], %1;\n"
        "@p bra LAB_DONE;\n"
        "mov.b32 n, 0;\n"
        "LAB_WAIT:\n"
        "mbarrier.try_wait.parity.shared::cta.b64 p, [%0], %1;\n"
        "@p bra LAB_DONE;\n"
        "add.u32 n, n, 1;\n"
        "setp.lt.u32 p, n, 0x40000;\n"
        "@p bra LAB_WAIT;\n"
        "trap;\n"
        "LAB_DONE:\n}\n" ::"r"(bar), "r"(parity) : "memory");
}
__device__ __forceinline__ void tma_load_2d(uint32_t dst, const CUtensorMap* tm, int c0, int c1, uint32_t bar) {
    asm volatile("cp.async.bulk.tensor.2d.shared::cluster.global.mbarrier::complete_tx::bytes [%0], [%1, {%2, %3}], [%4];"
                 ::"r"(dst), "l"(tm), "r"(c0), "r"(c1), "r"(bar) : "memory");
}
__device__ __forceinline__ void tma_prefetch_2d(const CUtensorMap* tm, int c0, int c1) {
    asm volatile("cp.async.bulk.prefetch.tensor.2d.L2.global [%0, {%1, %2}];" ::"l"(tm), "r"(c0), "r"(c1) : "memory");
}
__device__ __forceinline__ void bulk_load(uint32_t dst, const void* src, uint32_t bytes, uint32_t bar) {
    asm volatile("cp.async.bulk.shared::cluster.global.mbarrier::complete_tx::bytes [%0], [%1], %2, [%3];"
                 ::"r"(dst), "l"(src), "r"(bytes), "r"(bar) : "memory");
}
__device__ __forceinline__ void tma_store_3d(const CUtensorMap* tm, uint32_t src, int c0, int c1, int c2) {
    asm volatile("cp.async.bulk.tensor.3d.global.shared::cta.bulk_group [%0, {%2, %3, %4}], [%1];"
                 ::"l"(tm), "r"(src), "r"(c0), "r"(c1), "r"(c2) : "memory");
}
__device__ __forceinline__ void mbar_arrive_both(uint32_t bar) {
    asm volatile("{\n.reg .b32 ra;\nmapa.shared::cluster.u32 ra, %0, 0;\nmbarrier.arrive.shared::cluster.b64 _, [ra];\n"
                 "mapa.shared::cluster.u32 ra, %0, 1;\nmbarrier.arrive.shared::cluster.b64 _, [ra];\n}\n" ::"r"(bar) : "memory");
}
__device__ __forceinline__ void cluster_arrive() { asm volatile("barrier.cluster.arrive.relaxed.aligned;" ::: "memory"); }
__device__ __forceinline__ void cluster_wait() { asm volatile("barrier.cluster.wait.acquire.aligned;" ::: "memory"); }
__device__ __forceinline__ uint32_t mapa(uint32_t addr, uint32_t cta) {
    uint32_t r; asm("mapa.shared::cluster.u32 %0, %1, %2;" : "=r"(r) : "r"(addr), "r"(cta)); return r;
}
__device__ __forceinline__ void copy_to_peer(uint32_t addr, uint32_t bytes, uint32_t bar, uint32_t peer) {
    asm volatile("cp.async.bulk.shared::cluster.shared::cta.mbarrier::complete_tx::bytes [%0], [%1], %2, [%3];"
                 ::"r"(mapa(addr, peer)), "r"(addr), "r"(bytes), "r"(mapa(bar, peer)) : "memory");
}
__device__ __forceinline__ void wgmma_fence() { asm volatile("wgmma.fence.sync.aligned;" ::: "memory"); }
__device__ __forceinline__ void wgmma_commit() { asm volatile("wgmma.commit_group.sync.aligned;" ::: "memory"); }
template <int N> __device__ __forceinline__ void wgmma_wait() { asm volatile("wgmma.wait_group.sync.aligned %0;" ::"n"(N) : "memory"); }
__device__ __forceinline__ uint32_t pack_bf16(float lo, float hi) {
    uint32_t r; asm("cvt.rn.bf16x2.f32 %0, %1, %2;" : "=r"(r) : "f"(hi), "f"(lo)); return r;
}
__device__ __forceinline__ void stmatrix_x4(uint32_t addr, uint32_t a, uint32_t b, uint32_t c, uint32_t d) {
    asm volatile("stmatrix.sync.aligned.m8n8.x4.shared.b16 [%0], {%1, %2, %3, %4};" ::"r"(addr), "r"(a), "r"(b), "r"(c), "r"(d) : "memory");
}
__device__ __forceinline__ uint4 lds128(uint32_t a) {
    uint4 v; asm volatile("ld.shared.v4.b32 {%0, %1, %2, %3}, [%4];" : "=r"(v.x), "=r"(v.y), "=r"(v.z), "=r"(v.w) : "r"(a) : "memory"); return v;
}
__device__ __forceinline__ void sts128(uint32_t a, uint4 v) {
    asm volatile("st.shared.v4.b32 [%0], {%1, %2, %3, %4};" ::"r"(a), "r"(v.x), "r"(v.y), "r"(v.z), "r"(v.w) : "memory");
}
template <int NTHR> __device__ __forceinline__ void bar_arrive(int id) { asm volatile("bar.arrive %0, %1;" ::"r"(id), "n"(NTHR) : "memory"); }
template <int NTHR> __device__ __forceinline__ void bar_sync(int id) { asm volatile("bar.sync %0, %1;" ::"r"(id), "n"(NTHR) : "memory"); }
__device__ __forceinline__ uint32_t mul_bf16x2(uint32_t a, uint32_t b) { uint32_t r; asm("mul.rn.bf16x2 %0, %1, %2;" : "=r"(r) : "r"(a), "r"(b)); return r; }
__device__ __forceinline__ uint4 dequant8(const uint4& q0, const uint4& q1, const uint4& sc, uint32_t tab) {
    uint4 r;
    r.x = mul_bf16x2(__byte_perm(__shfl_sync(~0u, tab, q0.x), __shfl_sync(~0u, tab, q0.y), 0x5410), sc.x);
    r.y = mul_bf16x2(__byte_perm(__shfl_sync(~0u, tab, q0.z), __shfl_sync(~0u, tab, q0.w), 0x5410), sc.y);
    r.z = mul_bf16x2(__byte_perm(__shfl_sync(~0u, tab, q1.x), __shfl_sync(~0u, tab, q1.y), 0x5410), sc.z);
    r.w = mul_bf16x2(__byte_perm(__shfl_sync(~0u, tab, q1.z), __shfl_sync(~0u, tab, q1.w), 0x5410), sc.w);
    return r;
}
struct Lut { uint32_t lo[4], hi[4]; };
__device__ __forceinline__ uint32_t prmt(uint32_t a, uint32_t b, uint32_t s) { uint32_t r; asm("prmt.b32 %0, %1, %2, %3;" : "=r"(r) : "r"(a), "r"(b), "r"(s)); return r; }
__device__ __forceinline__ void lookup4(const uint4& q, const Lut& t, uint32_t& w01, uint32_t& w23) {
    uint32_t ab, cd, p;
    asm("mad.lo.u32 %0, %1, 16, %2;" : "=r"(ab) : "r"(q.y), "r"(q.x));
    asm("mad.lo.u32 %0, %1, 16, %2;" : "=r"(cd) : "r"(q.w), "r"(q.z));
    asm("mad.lo.u32 %0, %1, 256, %2;" : "=r"(p) : "r"(cd), "r"(ab));
    const uint32_t sel = ((p >> 1) & 0x4444u) | 0x3210u;
    const uint32_t s7 = p & 0x7777u;
    const uint32_t lo = prmt(prmt(t.lo[0], t.lo[1], p), prmt(t.lo[2], t.lo[3], s7), sel);
    const uint32_t hi = prmt(prmt(t.hi[0], t.hi[1], p), prmt(t.hi[2], t.hi[3], s7), sel);
    w01 = prmt(lo, hi, 0x5140);
    w23 = prmt(lo, hi, 0x7362);
}
__device__ __forceinline__ uint4 dequant8_alu(const uint4& q0, const uint4& q1, const uint4& sc, const Lut& t) {
    uint4 r;
    lookup4(q0, t, r.x, r.y);
    lookup4(q1, t, r.z, r.w);
    r.x = mul_bf16x2(r.x, sc.x); r.y = mul_bf16x2(r.y, sc.y); r.z = mul_bf16x2(r.z, sc.z); r.w = mul_bf16x2(r.w, sc.w);
    return r;
}
__device__ __forceinline__ void bulk_commit() { asm volatile("cp.async.bulk.commit_group;" ::: "memory"); }
template <int N> __device__ __forceinline__ void bulk_wait_read() { asm volatile("cp.async.bulk.wait_group.read %0;" ::"n"(N) : "memory"); }
__device__ __forceinline__ void fence_async_smem() { asm volatile("fence.proxy.async.shared::cta;" ::: "memory"); }

__device__ __forceinline__ bool mbar_try(uint32_t bar, uint32_t parity) {
    uint32_t ok;
    asm volatile("{\n.reg .pred p;\nmbarrier.try_wait.parity.shared::cta.b64 p, [%1], %2;\nselp.u32 %0, 1, 0, p;\n}\n" : "=r"(ok) : "r"(bar), "r"(parity) : "memory");
    return ok != 0;
}
__device__ __forceinline__ uint4 lds128p(uint32_t a, uint32_t on) {
    uint4 v;
    asm volatile("{\n.reg .pred p;\nsetp.ne.u32 p, %5, 0;\n@p ld.shared.v4.b32 {%0, %1, %2, %3}, [%4];\n}\n" : "=r"(v.x), "=r"(v.y), "=r"(v.z), "=r"(v.w) : "r"(a), "r"(on) : "memory");
    return v;
}
__device__ __forceinline__ void sts128p(uint32_t a, uint4 v, uint32_t on) {
    asm volatile("{\n.reg .pred p;\nsetp.ne.u32 p, %5, 0;\n@p st.shared.v4.b32 [%0], {%1, %2, %3, %4};\n}\n" ::"r"(a), "r"(v.x), "r"(v.y), "r"(v.z), "r"(v.w), "r"(on) : "memory");
}
__device__ __forceinline__ uint32_t pack4(const uint4& q) {
    uint32_t ab, cd, p;
    asm("mad.lo.u32 %0, %1, 16, %2;" : "=r"(ab) : "r"(q.y), "r"(q.x));
    asm("mad.lo.u32 %0, %1, 16, %2;" : "=r"(cd) : "r"(q.w), "r"(q.z));
    asm("mad.lo.u32 %0, %1, 256, %2;" : "=r"(p) : "r"(cd), "r"(ab));
    return p;
}
__device__ __forceinline__ uint32_t pack8(uint32_t lo, uint32_t hi) { uint32_t p; asm("mad.lo.u32 %0, %1, 65536, %2;" : "=r"(p) : "r"(hi), "r"(lo)); return p; }
__device__ __forceinline__ void lookup4s(uint32_t s7, uint32_t sel, const Lut& t, uint32_t& w01, uint32_t& w23) {
    const uint32_t lo = prmt(prmt(t.lo[0], t.lo[1], s7), prmt(t.lo[2], t.lo[3], s7), sel);
    const uint32_t hi = prmt(prmt(t.hi[0], t.hi[1], s7), prmt(t.hi[2], t.hi[3], s7), sel);
    w01 = prmt(lo, hi, 0x5140);
    w23 = prmt(lo, hi, 0x7362);
}
__device__ __forceinline__ uint4 dequant8p(uint32_t p, const uint4& sc, const Lut& t) {
    const uint32_t m8 = p & 0x88888888u, s7 = p & 0x77777777u;
    uint4 r;
    lookup4s(s7, (m8 >> 1) + 0x3210u, t, r.x, r.y);
    lookup4s(s7 >> 16, (m8 >> 17) + 0x3210u, t, r.z, r.w);
    r.x = mul_bf16x2(r.x, sc.x); r.y = mul_bf16x2(r.y, sc.y); r.z = mul_bf16x2(r.z, sc.z); r.w = mul_bf16x2(r.w, sc.w);
    return r;
}

__device__ __forceinline__ void mbar_wait2(uint32_t b0, uint32_t q0, uint32_t b1, uint32_t q1) {
    asm volatile(
        "{\n.reg .pred p0, p1;\n.reg .b32 n;\n"
        "mbarrier.try_wait.parity.shared::cta.b64 p0, [%0], %1;\n"
        "mbarrier.try_wait.parity.shared::cta.b64 p1, [%2], %3;\n"
        "and.pred p0, p0, p1;\n@p0 bra LAB_DONE;\n"
        "mov.b32 n, 0;\n"
        "LAB_WAIT:\n"
        "mbarrier.try_wait.parity.shared::cta.b64 p0, [%0], %1;\n"
        "mbarrier.try_wait.parity.shared::cta.b64 p1, [%2], %3;\n"
        "and.pred p0, p0, p1;\n@p0 bra LAB_DONE;\n"
        "add.u32 n, n, 1;\n"
        "setp.lt.u32 p0, n, 0x40000;\n"
        "@p0 bra LAB_WAIT;\n"
        "trap;\n"
        "LAB_DONE:\n}\n" ::"r"(b0), "r"(q0), "r"(b1), "r"(q1) : "memory");
}
__device__ __forceinline__ void mbar_wait3(uint32_t b0, uint32_t q0, uint32_t b1, uint32_t q1, uint32_t b2, uint32_t q2) {
    asm volatile(
        "{\n.reg .pred p0, p1, p2;\n.reg .b32 n;\n"
        "mbarrier.try_wait.parity.shared::cta.b64 p0, [%0], %1;\n"
        "mbarrier.try_wait.parity.shared::cta.b64 p1, [%2], %3;\n"
        "mbarrier.try_wait.parity.shared::cta.b64 p2, [%4], %5;\n"
        "and.pred p0, p0, p1;\nand.pred p0, p0, p2;\n@p0 bra LAB_DONE;\n"
        "mov.b32 n, 0;\n"
        "LAB_WAIT:\n"
        "mbarrier.try_wait.parity.shared::cta.b64 p0, [%0], %1;\n"
        "mbarrier.try_wait.parity.shared::cta.b64 p1, [%2], %3;\n"
        "mbarrier.try_wait.parity.shared::cta.b64 p2, [%4], %5;\n"
        "and.pred p0, p0, p1;\nand.pred p0, p0, p2;\n@p0 bra LAB_DONE;\n"
        "add.u32 n, n, 1;\n"
        "setp.lt.u32 p0, n, 0x40000;\n"
        "@p0 bra LAB_WAIT;\n"
        "trap;\n"
        "LAB_DONE:\n}\n" ::"r"(b0), "r"(q0), "r"(b1), "r"(q1), "r"(b2), "r"(q2) : "memory");
}
__device__ __forceinline__ void mbar_wait4(uint32_t b0, uint32_t q0, uint32_t b1, uint32_t q1, uint32_t b2, uint32_t q2, uint32_t b3, uint32_t q3) {
    asm volatile(
        "{\n.reg .pred p0, p1, p2, p3;\n.reg .b32 n;\n"
        "mbarrier.try_wait.parity.shared::cta.b64 p0, [%0], %1;\n"
        "mbarrier.try_wait.parity.shared::cta.b64 p1, [%2], %3;\n"
        "mbarrier.try_wait.parity.shared::cta.b64 p2, [%4], %5;\n"
        "mbarrier.try_wait.parity.shared::cta.b64 p3, [%6], %7;\n"
        "and.pred p0, p0, p1;\nand.pred p0, p0, p2;\nand.pred p0, p0, p3;\n@p0 bra LAB_DONE;\n"
        "mov.b32 n, 0;\n"
        "LAB_WAIT:\n"
        "mbarrier.try_wait.parity.shared::cta.b64 p0, [%0], %1;\n"
        "mbarrier.try_wait.parity.shared::cta.b64 p1, [%2], %3;\n"
        "mbarrier.try_wait.parity.shared::cta.b64 p2, [%4], %5;\n"
        "mbarrier.try_wait.parity.shared::cta.b64 p3, [%6], %7;\n"
        "and.pred p0, p0, p1;\nand.pred p0, p0, p2;\nand.pred p0, p0, p3;\n@p0 bra LAB_DONE;\n"
        "add.u32 n, n, 1;\n"
        "setp.lt.u32 p0, n, 0x40000;\n"
        "@p0 bra LAB_WAIT;\n"
        "trap;\n"
        "LAB_DONE:\n}\n" ::"r"(b0), "r"(q0), "r"(b1), "r"(q1), "r"(b2), "r"(q2), "r"(b3), "r"(q3) : "memory");
}

__device__ __forceinline__ uint32_t madi(uint32_t hi, uint32_t m, uint32_t lo) { uint32_t r; asm("mad.lo.u32 %0, %1, %2, %3;" : "=r"(r) : "r"(hi), "r"(m), "r"(lo)); return r; }
__device__ __forceinline__ void pack16(const uint4& a, const uint4& b, const uint4& c, const uint4& d, uint32_t& p1, uint32_t& p2) {
    p1 = madi(madi(madi(d.y, 65536, b.y), 256, madi(c.y, 65536, a.y)), 16, madi(madi(d.x, 256, c.x), 65536, madi(b.x, 256, a.x)));
    p2 = madi(madi(madi(d.w, 256, c.w), 65536, madi(b.w, 256, a.w)), 16, madi(madi(c.z, 256, b.z), 256, madi(d.z, 1 << 24, a.z)));
}
template <int HI>
__device__ __forceinline__ uint4 dequant16(uint32_t p1, uint32_t p2, const uint4& sc, const Lut& t) {
    uint4 r;
    lookup4s((p1 & 0x77777777u) >> (16 * HI), ((p1 & 0x88888888u) >> (16 * HI + 1)) + 0x3210u, t, r.x, r.z);
    lookup4s((p2 & 0x77777777u) >> (16 * HI), ((p2 & 0x88888888u) >> (16 * HI + 1)) + 0x3210u, t, r.y, r.w);
    r.x = mul_bf16x2(r.x, sc.x); r.y = mul_bf16x2(r.y, sc.y); r.z = mul_bf16x2(r.z, sc.z); r.w = mul_bf16x2(r.w, sc.w);
    return r;
}

__device__ __forceinline__ void bulk_load_mc(uint32_t dst, const void* src, uint32_t bytes, uint32_t bar) {
    asm volatile("cp.async.bulk.shared::cluster.global.mbarrier::complete_tx::bytes.multicast::cluster [%0], [%1], %2, [%3], %4;"
                 ::"r"(dst), "l"(src), "r"(bytes), "r"(bar), "h"((uint16_t)3) : "memory");
}
__device__ __forceinline__ unsigned store_probed(void* p, uint4 v) {
    unsigned r;
    asm volatile("st.global.v4.b32 [%1], {%2, %3, %4, %5};\natom.relaxed.gpu.global.exch.b32 %0, [%1], %2;"
                 : "=r"(r) : "l"(p), "r"(v.x), "r"(v.y), "r"(v.z), "r"(v.w) : "memory");
    return r;
}
__device__ __forceinline__ unsigned after(unsigned n, unsigned p, unsigned z) {
    unsigned r; asm volatile("lop3.b32 %0, %1, %2, %3, 0xea;" : "=r"(r) : "r"(p), "r"(z), "r"(n)); return r;
}
__device__ __forceinline__ void red_add(unsigned* f, unsigned n) { asm volatile("red.relaxed.gpu.global.add.u32 [%0], %1;" ::"l"(f), "r"(n) : "memory"); }
__device__ __forceinline__ unsigned ld_relaxed(const unsigned* p) {
    unsigned v; asm volatile("ld.relaxed.gpu.global.u32 %0, [%1];" : "=r"(v) : "l"(p) : "memory"); return v;
}

__device__ __forceinline__ void tma_load_3d(uint32_t dst, const CUtensorMap* tm, int c0, int c1, int c2, uint32_t bar) {
    asm volatile("cp.async.bulk.tensor.3d.shared::cluster.global.mbarrier::complete_tx::bytes [%0], [%1, {%2, %3, %4}], [%5];"
                 ::"r"(dst), "l"(tm), "r"(c0), "r"(c1), "r"(c2), "r"(bar) : "memory");
}
__device__ __forceinline__ void tma_store_2d(const CUtensorMap* tm, uint32_t src, int c0, int c1) {
    asm volatile("cp.async.bulk.tensor.2d.global.shared::cta.bulk_group [%0, {%2, %3}], [%1];"
                 ::"l"(tm), "r"(src), "r"(c0), "r"(c1) : "memory");
}
__device__ __forceinline__ void mbar_arrive_n(uint32_t bar, uint32_t n) { asm volatile("mbarrier.arrive.shared::cta.b64 _, [%0], %1;" ::"r"(bar), "r"(n) : "memory"); }

__device__ __forceinline__ uint2 lds64(uint32_t a) {
    uint2 v; asm volatile("ld.shared.v2.b32 {%0, %1}, [%2];" : "=r"(v.x), "=r"(v.y) : "r"(a) : "memory"); return v;
}
__device__ __forceinline__ uint32_t lds32(uint32_t a) {
    uint32_t v; asm volatile("ld.shared.b32 %0, [%1];" : "=r"(v) : "r"(a) : "memory"); return v;
}
__device__ __forceinline__ void st_async128(uint32_t raddr, uint4 v, uint32_t rbar) {
    asm volatile("st.async.shared::cluster.mbarrier::complete_tx::bytes.v4.b32 [%0], {%1, %2, %3, %4}, [%5];"
                 ::"r"(raddr), "r"(v.x), "r"(v.y), "r"(v.z), "r"(v.w), "r"(rbar) : "memory");
}
__device__ __forceinline__ void stg128(void* p, uint32_t a, uint32_t b, uint32_t c, uint32_t d) {
    asm volatile("st.global.v4.b32 [%0], {%1, %2, %3, %4};" ::"l"(p), "r"(a), "r"(b), "r"(c), "r"(d) : "memory");
}

__device__ __forceinline__ void tma_prefetch_3d(const CUtensorMap* tm, int c0, int c1, int c2) {
    asm volatile("cp.async.bulk.prefetch.tensor.3d.L2.global [%0, {%1, %2, %3}];" ::"l"(tm), "r"(c0), "r"(c1), "r"(c2) : "memory");
}
__device__ __forceinline__ void sts32(uint32_t a, uint32_t v) { asm volatile("st.shared.b32 [%0], %1;" ::"r"(a), "r"(v) : "memory"); }
__device__ __forceinline__ void stg32(void* p, uint32_t v) { asm volatile("st.global.b32 [%0], %1;" ::"l"(p), "r"(v) : "memory"); }
__device__ __forceinline__ void probe_l2(uint32_t dst, const void* src, uint32_t on) {
    asm volatile("{\n.reg .pred p;\nsetp.ne.u32 p, %2, 0;\n@p cp.async.cg.shared.global [%0], [%1], 16;\n}\ncp.async.commit_group;" ::"r"(dst), "l"(src), "r"(on) : "memory");
}
template <int N> __device__ __forceinline__ void probe_wait() { asm volatile("cp.async.wait_group %0;" ::"n"(N) : "memory"); }

__device__ __forceinline__ void probe_arrive(uint32_t bar) { asm volatile("cp.async.mbarrier.arrive.noinc.shared::cta.b64 [%0];" ::"r"(bar) : "memory"); }
__device__ __forceinline__ void poll_ge(const unsigned* f, unsigned v, unsigned ready) {
    asm volatile(
        "{\n.reg .pred p;\n.reg .b32 v, n;\n"
        "setp.lt.u32 p, %1, %2;\n"
        "vote.sync.any.pred p, p, 0xffffffff;\n"
        "@!p bra.uni LAB_DONE;\n"
        "mov.b32 n, 0;\n"
        "LAB_POLL:\n"
        "ld.relaxed.gpu.global.u32 v, [%0];\n"
        "setp.lt.u32 p, v, %2;\n"
        "vote.sync.any.pred p, p, 0xffffffff;\n"
        "@!p bra.uni LAB_DONE;\n"
        "add.u32 n, n, 1;\n"
        "setp.lt.u32 p, n, 0x400000;\n"
        "@p bra.uni LAB_POLL;\n"
        "LAB_DONE:\n}\n" ::"l"(f), "r"(v), "r"(ready) : "memory");
}

__device__ __forceinline__ void delay(unsigned clks) {
    asm volatile(
        "{\n.reg .pred p;\n.reg .b32 t0, t;\n"
        "mov.u32 t0, %%clock;\n"
        "LAB_DELAY:\n"
        "mov.u32 t, %%clock;\n"
        "sub.u32 t, t, t0;\n"
        "setp.lt.u32 p, t, %0;\n"
        "vote.sync.any.pred p, p, 0xffffffff;\n"
        "@p bra.uni LAB_DELAY;\n}\n" ::"r"(clks) : "memory");
}

template <int I> struct IC { static constexpr int value = I; };
template <int I, int N, class F> __device__ __forceinline__ void static_for(F&& f) {
    if constexpr (I < N) { f(IC<I>{}); static_for<I + 1, N>(f); }
}

__device__ __forceinline__ uint4 ldmatrix_x4(uint32_t a) {
    uint4 v;
    asm volatile("ldmatrix.sync.aligned.m8n8.x4.shared.b16 {%0, %1, %2, %3}, [%4];" : "=r"(v.x), "=r"(v.y), "=r"(v.z), "=r"(v.w) : "r"(a) : "memory");
    return v;
}

template <int SCALE_D>
__device__ __forceinline__ void wgmma_ss(float (&d)[112], uint32_t descA, uint32_t descB) {
    asm volatile(
        "{\n.reg .pred p;\n.reg .b64 da, db;\nsetp.ne.b32 p, %114, 0;\n"
        "mov.b64 da, {%112, 0x40000040};\nmov.b64 db, {%113, 0x10};\n"
        "wgmma.mma_async.sync.aligned.m64n224k16.f32.bf16.bf16 "
        "{%0, %1, %2, %3, %4, %5, %6, %7, %8, %9, %10, %11, %12, %13, %14, %15, "
        "%16, %17, %18, %19, %20, %21, %22, %23, %24, %25, %26, %27, %28, %29, %30, %31, "
        "%32, %33, %34, %35, %36, %37, %38, %39, %40, %41, %42, %43, %44, %45, %46, %47, "
        "%48, %49, %50, %51, %52, %53, %54, %55, %56, %57, %58, %59, %60, %61, %62, %63, "
        "%64, %65, %66, %67, %68, %69, %70, %71, %72, %73, %74, %75, %76, %77, %78, %79, "
        "%80, %81, %82, %83, %84, %85, %86, %87, %88, %89, %90, %91, %92, %93, %94, %95, "
        "%96, %97, %98, %99, %100, %101, %102, %103, %104, %105, %106, %107, %108, %109, %110, %111}, "
        "da, db, p, 1, 1, 0, 1;\n}\n"
        : "+f"(d[0]), "+f"(d[1]), "+f"(d[2]), "+f"(d[3]), "+f"(d[4]), "+f"(d[5]), "+f"(d[6]), "+f"(d[7]),
          "+f"(d[8]), "+f"(d[9]), "+f"(d[10]), "+f"(d[11]), "+f"(d[12]), "+f"(d[13]), "+f"(d[14]), "+f"(d[15]),
          "+f"(d[16]), "+f"(d[17]), "+f"(d[18]), "+f"(d[19]), "+f"(d[20]), "+f"(d[21]), "+f"(d[22]), "+f"(d[23]),
          "+f"(d[24]), "+f"(d[25]), "+f"(d[26]), "+f"(d[27]), "+f"(d[28]), "+f"(d[29]), "+f"(d[30]), "+f"(d[31]),
          "+f"(d[32]), "+f"(d[33]), "+f"(d[34]), "+f"(d[35]), "+f"(d[36]), "+f"(d[37]), "+f"(d[38]), "+f"(d[39]),
          "+f"(d[40]), "+f"(d[41]), "+f"(d[42]), "+f"(d[43]), "+f"(d[44]), "+f"(d[45]), "+f"(d[46]), "+f"(d[47]),
          "+f"(d[48]), "+f"(d[49]), "+f"(d[50]), "+f"(d[51]), "+f"(d[52]), "+f"(d[53]), "+f"(d[54]), "+f"(d[55]),
          "+f"(d[56]), "+f"(d[57]), "+f"(d[58]), "+f"(d[59]), "+f"(d[60]), "+f"(d[61]), "+f"(d[62]), "+f"(d[63]),
          "+f"(d[64]), "+f"(d[65]), "+f"(d[66]), "+f"(d[67]), "+f"(d[68]), "+f"(d[69]), "+f"(d[70]), "+f"(d[71]),
          "+f"(d[72]), "+f"(d[73]), "+f"(d[74]), "+f"(d[75]), "+f"(d[76]), "+f"(d[77]), "+f"(d[78]), "+f"(d[79]),
          "+f"(d[80]), "+f"(d[81]), "+f"(d[82]), "+f"(d[83]), "+f"(d[84]), "+f"(d[85]), "+f"(d[86]), "+f"(d[87]),
          "+f"(d[88]), "+f"(d[89]), "+f"(d[90]), "+f"(d[91]), "+f"(d[92]), "+f"(d[93]), "+f"(d[94]), "+f"(d[95]),
          "+f"(d[96]), "+f"(d[97]), "+f"(d[98]), "+f"(d[99]), "+f"(d[100]), "+f"(d[101]), "+f"(d[102]), "+f"(d[103]),
          "+f"(d[104]), "+f"(d[105]), "+f"(d[106]), "+f"(d[107]), "+f"(d[108]), "+f"(d[109]), "+f"(d[110]), "+f"(d[111])
        : "r"(descA), "r"(descB), "n"(SCALE_D));
}

template <int SCALE_D>
__device__ __forceinline__ void wgmma_ss(float (&d)[80], uint32_t descA, uint32_t descB) {
    asm volatile(
        "{\n.reg .pred p;\n.reg .b64 da, db;\nsetp.ne.b32 p, %82, 0;\n"
        "mov.b64 da, {%80, 0x40000040};\nmov.b64 db, {%81, 0x10};\n"
        "wgmma.mma_async.sync.aligned.m64n160k16.f32.bf16.bf16 "
        "{%0, %1, %2, %3, %4, %5, %6, %7, %8, %9, %10, %11, %12, %13, %14, %15, "
        "%16, %17, %18, %19, %20, %21, %22, %23, %24, %25, %26, %27, %28, %29, %30, %31, "
        "%32, %33, %34, %35, %36, %37, %38, %39, %40, %41, %42, %43, %44, %45, %46, %47, "
        "%48, %49, %50, %51, %52, %53, %54, %55, %56, %57, %58, %59, %60, %61, %62, %63, "
        "%64, %65, %66, %67, %68, %69, %70, %71, %72, %73, %74, %75, %76, %77, %78, %79}, "
        "da, db, p, 1, 1, 0, 1;\n}\n"
        : "+f"(d[0]), "+f"(d[1]), "+f"(d[2]), "+f"(d[3]), "+f"(d[4]), "+f"(d[5]), "+f"(d[6]), "+f"(d[7]),
          "+f"(d[8]), "+f"(d[9]), "+f"(d[10]), "+f"(d[11]), "+f"(d[12]), "+f"(d[13]), "+f"(d[14]), "+f"(d[15]),
          "+f"(d[16]), "+f"(d[17]), "+f"(d[18]), "+f"(d[19]), "+f"(d[20]), "+f"(d[21]), "+f"(d[22]), "+f"(d[23]),
          "+f"(d[24]), "+f"(d[25]), "+f"(d[26]), "+f"(d[27]), "+f"(d[28]), "+f"(d[29]), "+f"(d[30]), "+f"(d[31]),
          "+f"(d[32]), "+f"(d[33]), "+f"(d[34]), "+f"(d[35]), "+f"(d[36]), "+f"(d[37]), "+f"(d[38]), "+f"(d[39]),
          "+f"(d[40]), "+f"(d[41]), "+f"(d[42]), "+f"(d[43]), "+f"(d[44]), "+f"(d[45]), "+f"(d[46]), "+f"(d[47]),
          "+f"(d[48]), "+f"(d[49]), "+f"(d[50]), "+f"(d[51]), "+f"(d[52]), "+f"(d[53]), "+f"(d[54]), "+f"(d[55]),
          "+f"(d[56]), "+f"(d[57]), "+f"(d[58]), "+f"(d[59]), "+f"(d[60]), "+f"(d[61]), "+f"(d[62]), "+f"(d[63]),
          "+f"(d[64]), "+f"(d[65]), "+f"(d[66]), "+f"(d[67]), "+f"(d[68]), "+f"(d[69]), "+f"(d[70]), "+f"(d[71]),
          "+f"(d[72]), "+f"(d[73]), "+f"(d[74]), "+f"(d[75]), "+f"(d[76]), "+f"(d[77]), "+f"(d[78]), "+f"(d[79])
        : "r"(descA), "r"(descB), "n"(SCALE_D));
}

template <int SCALE_D>
__device__ __forceinline__ void wgmma_ss(float (&d)[64], uint32_t descA, uint32_t descB) {
    asm volatile(
        "{\n.reg .pred p;\n.reg .b64 da, db;\nsetp.ne.b32 p, %66, 0;\n"
        "mov.b64 da, {%64, 0x40000040};\nmov.b64 db, {%65, 0x10};\n"
        "wgmma.mma_async.sync.aligned.m64n128k16.f32.bf16.bf16 "
        "{%0, %1, %2, %3, %4, %5, %6, %7, %8, %9, %10, %11, %12, %13, %14, %15, "
        "%16, %17, %18, %19, %20, %21, %22, %23, %24, %25, %26, %27, %28, %29, %30, %31, "
        "%32, %33, %34, %35, %36, %37, %38, %39, %40, %41, %42, %43, %44, %45, %46, %47, "
        "%48, %49, %50, %51, %52, %53, %54, %55, %56, %57, %58, %59, %60, %61, %62, %63}, "
        "da, db, p, 1, 1, 0, 1;\n}\n"
        : "+f"(d[0]), "+f"(d[1]), "+f"(d[2]), "+f"(d[3]), "+f"(d[4]), "+f"(d[5]), "+f"(d[6]), "+f"(d[7]),
          "+f"(d[8]), "+f"(d[9]), "+f"(d[10]), "+f"(d[11]), "+f"(d[12]), "+f"(d[13]), "+f"(d[14]), "+f"(d[15]),
          "+f"(d[16]), "+f"(d[17]), "+f"(d[18]), "+f"(d[19]), "+f"(d[20]), "+f"(d[21]), "+f"(d[22]), "+f"(d[23]),
          "+f"(d[24]), "+f"(d[25]), "+f"(d[26]), "+f"(d[27]), "+f"(d[28]), "+f"(d[29]), "+f"(d[30]), "+f"(d[31]),
          "+f"(d[32]), "+f"(d[33]), "+f"(d[34]), "+f"(d[35]), "+f"(d[36]), "+f"(d[37]), "+f"(d[38]), "+f"(d[39]),
          "+f"(d[40]), "+f"(d[41]), "+f"(d[42]), "+f"(d[43]), "+f"(d[44]), "+f"(d[45]), "+f"(d[46]), "+f"(d[47]),
          "+f"(d[48]), "+f"(d[49]), "+f"(d[50]), "+f"(d[51]), "+f"(d[52]), "+f"(d[53]), "+f"(d[54]), "+f"(d[55]),
          "+f"(d[56]), "+f"(d[57]), "+f"(d[58]), "+f"(d[59]), "+f"(d[60]), "+f"(d[61]), "+f"(d[62]), "+f"(d[63])
        : "r"(descA), "r"(descB), "n"(SCALE_D));
}

template <int SCALE_D>
__device__ __forceinline__ void wgmma_ss(float (&d)[48], uint32_t descA, uint32_t descB) {
    asm volatile(
        "{\n.reg .pred p;\n.reg .b64 da, db;\nsetp.ne.b32 p, %50, 0;\n"
        "mov.b64 da, {%48, 0x40000040};\nmov.b64 db, {%49, 0x10};\n"
        "wgmma.mma_async.sync.aligned.m64n96k16.f32.bf16.bf16 "
        "{%0, %1, %2, %3, %4, %5, %6, %7, %8, %9, %10, %11, %12, %13, %14, %15, "
        "%16, %17, %18, %19, %20, %21, %22, %23, %24, %25, %26, %27, %28, %29, %30, %31, "
        "%32, %33, %34, %35, %36, %37, %38, %39, %40, %41, %42, %43, %44, %45, %46, %47}, "
        "da, db, p, 1, 1, 0, 1;\n}\n"
        : "+f"(d[0]), "+f"(d[1]), "+f"(d[2]), "+f"(d[3]), "+f"(d[4]), "+f"(d[5]), "+f"(d[6]), "+f"(d[7]),
          "+f"(d[8]), "+f"(d[9]), "+f"(d[10]), "+f"(d[11]), "+f"(d[12]), "+f"(d[13]), "+f"(d[14]), "+f"(d[15]),
          "+f"(d[16]), "+f"(d[17]), "+f"(d[18]), "+f"(d[19]), "+f"(d[20]), "+f"(d[21]), "+f"(d[22]), "+f"(d[23]),
          "+f"(d[24]), "+f"(d[25]), "+f"(d[26]), "+f"(d[27]), "+f"(d[28]), "+f"(d[29]), "+f"(d[30]), "+f"(d[31]),
          "+f"(d[32]), "+f"(d[33]), "+f"(d[34]), "+f"(d[35]), "+f"(d[36]), "+f"(d[37]), "+f"(d[38]), "+f"(d[39]),
          "+f"(d[40]), "+f"(d[41]), "+f"(d[42]), "+f"(d[43]), "+f"(d[44]), "+f"(d[45]), "+f"(d[46]), "+f"(d[47])
        : "r"(descA), "r"(descB), "n"(SCALE_D));
}

template <int SCALE_D>
__device__ __forceinline__ void wgmma_ss(float (&d)[32], uint32_t descA, uint32_t descB) {
    asm volatile(
        "{\n.reg .pred p;\n.reg .b64 da, db;\nsetp.ne.b32 p, %34, 0;\n"
        "mov.b64 da, {%32, 0x40000040};\nmov.b64 db, {%33, 0x10};\n"
        "wgmma.mma_async.sync.aligned.m64n64k16.f32.bf16.bf16 "
        "{%0, %1, %2, %3, %4, %5, %6, %7, %8, %9, %10, %11, %12, %13, %14, %15, "
        "%16, %17, %18, %19, %20, %21, %22, %23, %24, %25, %26, %27, %28, %29, %30, %31}, "
        "da, db, p, 1, 1, 0, 1;\n}\n"
        : "+f"(d[0]), "+f"(d[1]), "+f"(d[2]), "+f"(d[3]), "+f"(d[4]), "+f"(d[5]), "+f"(d[6]), "+f"(d[7]),
          "+f"(d[8]), "+f"(d[9]), "+f"(d[10]), "+f"(d[11]), "+f"(d[12]), "+f"(d[13]), "+f"(d[14]), "+f"(d[15]),
          "+f"(d[16]), "+f"(d[17]), "+f"(d[18]), "+f"(d[19]), "+f"(d[20]), "+f"(d[21]), "+f"(d[22]), "+f"(d[23]),
          "+f"(d[24]), "+f"(d[25]), "+f"(d[26]), "+f"(d[27]), "+f"(d[28]), "+f"(d[29]), "+f"(d[30]), "+f"(d[31])
        : "r"(descA), "r"(descB), "n"(SCALE_D));
}

template <int SCALE_D>
__device__ __forceinline__ void wgmma_ss(float (&d)[16], uint32_t descA, uint32_t descB) {
    asm volatile(
        "{\n.reg .pred p;\n.reg .b64 da, db;\nsetp.ne.b32 p, %18, 0;\n"
        "mov.b64 da, {%16, 0x40000040};\nmov.b64 db, {%17, 0x10};\n"
        "wgmma.mma_async.sync.aligned.m64n32k16.f32.bf16.bf16 "
        "{%0, %1, %2, %3, %4, %5, %6, %7, %8, %9, %10, %11, %12, %13, %14, %15}, "
        "da, db, p, 1, 1, 0, 1;\n}\n"
        : "+f"(d[0]), "+f"(d[1]), "+f"(d[2]), "+f"(d[3]), "+f"(d[4]), "+f"(d[5]), "+f"(d[6]), "+f"(d[7]),
          "+f"(d[8]), "+f"(d[9]), "+f"(d[10]), "+f"(d[11]), "+f"(d[12]), "+f"(d[13]), "+f"(d[14]), "+f"(d[15])
        : "r"(descA), "r"(descB), "n"(SCALE_D));
}

__device__ __forceinline__ void wgmma_rs(float (&d)[80], const uint4& a, uint32_t descB) {
    asm volatile(
        "{\n.reg .pred p;\n.reg .b64 db;\nsetp.eq.b32 p, 0, 0;\n"
        "mov.b64 db, {%84, 0x10};\n"
        "wgmma.mma_async.sync.aligned.m64n160k16.f32.bf16.bf16 "
        "{%0, %1, %2, %3, %4, %5, %6, %7, %8, %9, %10, %11, %12, %13, %14, %15, "
        "%16, %17, %18, %19, %20, %21, %22, %23, %24, %25, %26, %27, %28, %29, %30, %31, "
        "%32, %33, %34, %35, %36, %37, %38, %39, %40, %41, %42, %43, %44, %45, %46, %47, "
        "%48, %49, %50, %51, %52, %53, %54, %55, %56, %57, %58, %59, %60, %61, %62, %63, "
        "%64, %65, %66, %67, %68, %69, %70, %71, %72, %73, %74, %75, %76, %77, %78, %79}, "
        "{%80, %81, %82, %83}, db, p, 1, 1, 1;\n}\n"
        : "+f"(d[0]), "+f"(d[1]), "+f"(d[2]), "+f"(d[3]), "+f"(d[4]), "+f"(d[5]), "+f"(d[6]), "+f"(d[7]),
          "+f"(d[8]), "+f"(d[9]), "+f"(d[10]), "+f"(d[11]), "+f"(d[12]), "+f"(d[13]), "+f"(d[14]), "+f"(d[15]),
          "+f"(d[16]), "+f"(d[17]), "+f"(d[18]), "+f"(d[19]), "+f"(d[20]), "+f"(d[21]), "+f"(d[22]), "+f"(d[23]),
          "+f"(d[24]), "+f"(d[25]), "+f"(d[26]), "+f"(d[27]), "+f"(d[28]), "+f"(d[29]), "+f"(d[30]), "+f"(d[31]),
          "+f"(d[32]), "+f"(d[33]), "+f"(d[34]), "+f"(d[35]), "+f"(d[36]), "+f"(d[37]), "+f"(d[38]), "+f"(d[39]),
          "+f"(d[40]), "+f"(d[41]), "+f"(d[42]), "+f"(d[43]), "+f"(d[44]), "+f"(d[45]), "+f"(d[46]), "+f"(d[47]),
          "+f"(d[48]), "+f"(d[49]), "+f"(d[50]), "+f"(d[51]), "+f"(d[52]), "+f"(d[53]), "+f"(d[54]), "+f"(d[55]),
          "+f"(d[56]), "+f"(d[57]), "+f"(d[58]), "+f"(d[59]), "+f"(d[60]), "+f"(d[61]), "+f"(d[62]), "+f"(d[63]),
          "+f"(d[64]), "+f"(d[65]), "+f"(d[66]), "+f"(d[67]), "+f"(d[68]), "+f"(d[69]), "+f"(d[70]), "+f"(d[71]),
          "+f"(d[72]), "+f"(d[73]), "+f"(d[74]), "+f"(d[75]), "+f"(d[76]), "+f"(d[77]), "+f"(d[78]), "+f"(d[79])
        : "r"(a.x), "r"(a.y), "r"(a.z), "r"(a.w), "r"(descB));
}

__device__ __forceinline__ void wgmma_rs(float (&d)[64], const uint4& a, uint32_t descB) {
    asm volatile(
        "{\n.reg .pred p;\n.reg .b64 db;\nsetp.eq.b32 p, 0, 0;\n"
        "mov.b64 db, {%68, 0x10};\n"
        "wgmma.mma_async.sync.aligned.m64n128k16.f32.bf16.bf16 "
        "{%0, %1, %2, %3, %4, %5, %6, %7, %8, %9, %10, %11, %12, %13, %14, %15, "
        "%16, %17, %18, %19, %20, %21, %22, %23, %24, %25, %26, %27, %28, %29, %30, %31, "
        "%32, %33, %34, %35, %36, %37, %38, %39, %40, %41, %42, %43, %44, %45, %46, %47, "
        "%48, %49, %50, %51, %52, %53, %54, %55, %56, %57, %58, %59, %60, %61, %62, %63}, "
        "{%64, %65, %66, %67}, db, p, 1, 1, 1;\n}\n"
        : "+f"(d[0]), "+f"(d[1]), "+f"(d[2]), "+f"(d[3]), "+f"(d[4]), "+f"(d[5]), "+f"(d[6]), "+f"(d[7]),
          "+f"(d[8]), "+f"(d[9]), "+f"(d[10]), "+f"(d[11]), "+f"(d[12]), "+f"(d[13]), "+f"(d[14]), "+f"(d[15]),
          "+f"(d[16]), "+f"(d[17]), "+f"(d[18]), "+f"(d[19]), "+f"(d[20]), "+f"(d[21]), "+f"(d[22]), "+f"(d[23]),
          "+f"(d[24]), "+f"(d[25]), "+f"(d[26]), "+f"(d[27]), "+f"(d[28]), "+f"(d[29]), "+f"(d[30]), "+f"(d[31]),
          "+f"(d[32]), "+f"(d[33]), "+f"(d[34]), "+f"(d[35]), "+f"(d[36]), "+f"(d[37]), "+f"(d[38]), "+f"(d[39]),
          "+f"(d[40]), "+f"(d[41]), "+f"(d[42]), "+f"(d[43]), "+f"(d[44]), "+f"(d[45]), "+f"(d[46]), "+f"(d[47]),
          "+f"(d[48]), "+f"(d[49]), "+f"(d[50]), "+f"(d[51]), "+f"(d[52]), "+f"(d[53]), "+f"(d[54]), "+f"(d[55]),
          "+f"(d[56]), "+f"(d[57]), "+f"(d[58]), "+f"(d[59]), "+f"(d[60]), "+f"(d[61]), "+f"(d[62]), "+f"(d[63])
        : "r"(a.x), "r"(a.y), "r"(a.z), "r"(a.w), "r"(descB));
}

__device__ __forceinline__ void wgmma_rs(float (&d)[48], const uint4& a, uint32_t descB) {
    asm volatile(
        "{\n.reg .pred p;\n.reg .b64 db;\nsetp.eq.b32 p, 0, 0;\n"
        "mov.b64 db, {%52, 0x10};\n"
        "wgmma.mma_async.sync.aligned.m64n96k16.f32.bf16.bf16 "
        "{%0, %1, %2, %3, %4, %5, %6, %7, %8, %9, %10, %11, %12, %13, %14, %15, "
        "%16, %17, %18, %19, %20, %21, %22, %23, %24, %25, %26, %27, %28, %29, %30, %31, "
        "%32, %33, %34, %35, %36, %37, %38, %39, %40, %41, %42, %43, %44, %45, %46, %47}, "
        "{%48, %49, %50, %51}, db, p, 1, 1, 1;\n}\n"
        : "+f"(d[0]), "+f"(d[1]), "+f"(d[2]), "+f"(d[3]), "+f"(d[4]), "+f"(d[5]), "+f"(d[6]), "+f"(d[7]),
          "+f"(d[8]), "+f"(d[9]), "+f"(d[10]), "+f"(d[11]), "+f"(d[12]), "+f"(d[13]), "+f"(d[14]), "+f"(d[15]),
          "+f"(d[16]), "+f"(d[17]), "+f"(d[18]), "+f"(d[19]), "+f"(d[20]), "+f"(d[21]), "+f"(d[22]), "+f"(d[23]),
          "+f"(d[24]), "+f"(d[25]), "+f"(d[26]), "+f"(d[27]), "+f"(d[28]), "+f"(d[29]), "+f"(d[30]), "+f"(d[31]),
          "+f"(d[32]), "+f"(d[33]), "+f"(d[34]), "+f"(d[35]), "+f"(d[36]), "+f"(d[37]), "+f"(d[38]), "+f"(d[39]),
          "+f"(d[40]), "+f"(d[41]), "+f"(d[42]), "+f"(d[43]), "+f"(d[44]), "+f"(d[45]), "+f"(d[46]), "+f"(d[47])
        : "r"(a.x), "r"(a.y), "r"(a.z), "r"(a.w), "r"(descB));
}

__device__ __forceinline__ void wgmma_rs(float (&d)[32], const uint4& a, uint32_t descB) {
    asm volatile(
        "{\n.reg .pred p;\n.reg .b64 db;\nsetp.eq.b32 p, 0, 0;\n"
        "mov.b64 db, {%36, 0x10};\n"
        "wgmma.mma_async.sync.aligned.m64n64k16.f32.bf16.bf16 "
        "{%0, %1, %2, %3, %4, %5, %6, %7, %8, %9, %10, %11, %12, %13, %14, %15, "
        "%16, %17, %18, %19, %20, %21, %22, %23, %24, %25, %26, %27, %28, %29, %30, %31}, "
        "{%32, %33, %34, %35}, db, p, 1, 1, 1;\n}\n"
        : "+f"(d[0]), "+f"(d[1]), "+f"(d[2]), "+f"(d[3]), "+f"(d[4]), "+f"(d[5]), "+f"(d[6]), "+f"(d[7]),
          "+f"(d[8]), "+f"(d[9]), "+f"(d[10]), "+f"(d[11]), "+f"(d[12]), "+f"(d[13]), "+f"(d[14]), "+f"(d[15]),
          "+f"(d[16]), "+f"(d[17]), "+f"(d[18]), "+f"(d[19]), "+f"(d[20]), "+f"(d[21]), "+f"(d[22]), "+f"(d[23]),
          "+f"(d[24]), "+f"(d[25]), "+f"(d[26]), "+f"(d[27]), "+f"(d[28]), "+f"(d[29]), "+f"(d[30]), "+f"(d[31])
        : "r"(a.x), "r"(a.y), "r"(a.z), "r"(a.w), "r"(descB));
}

__device__ __forceinline__ void wgmma_rs(float (&d)[16], const uint4& a, uint32_t descB) {
    asm volatile(
        "{\n.reg .pred p;\n.reg .b64 db;\nsetp.eq.b32 p, 0, 0;\n"
        "mov.b64 db, {%20, 0x10};\n"
        "wgmma.mma_async.sync.aligned.m64n32k16.f32.bf16.bf16 "
        "{%0, %1, %2, %3, %4, %5, %6, %7, %8, %9, %10, %11, %12, %13, %14, %15}, "
        "{%16, %17, %18, %19}, db, p, 1, 1, 1;\n}\n"
        : "+f"(d[0]), "+f"(d[1]), "+f"(d[2]), "+f"(d[3]), "+f"(d[4]), "+f"(d[5]), "+f"(d[6]), "+f"(d[7]),
          "+f"(d[8]), "+f"(d[9]), "+f"(d[10]), "+f"(d[11]), "+f"(d[12]), "+f"(d[13]), "+f"(d[14]), "+f"(d[15])
        : "r"(a.x), "r"(a.y), "r"(a.z), "r"(a.w), "r"(descB));
}

#define F1A 1
#define R1E 1
#define ORD 1
#define PF1 1
#define PF3 0
#define PF4 1
#define W2U 1
#define PFX 1
#define SS 0
#define WS 1
#define S7U 5
#define LATERING 1
#define PFV 3
#define W4U 5
#define DLY2 0
#define DLY3 0
#define LATES 5
#define S2REAL 1
#define PACE1 1100
#define PACE2 1700
#define W3U 4
#define TM(i) TC(i)
#define TD(i)
__device__ __forceinline__ uint32_t pack8x(const uint4& a, const uint4& b) {
    return madi(madi(madi(b.w, 65536, a.w), 16, madi(b.z, 65536, a.z)), 256, madi(madi(b.y, 65536, a.y), 16, madi(b.x, 65536, a.x)));
}
constexpr int NT = N_ / BN, MT = M_ / BM;
constexpr int W_BYTES = BN * BK * 2;
constexpr int X_OFF = 0;
constexpr int W_OFF = 81920;
constexpr int R_OFF = W_OFF + 4 * W_BYTES;
constexpr int SC_OFF = R_OFF + W_BYTES - 896;
constexpr int EARLY_OFF = W_OFF + 2 * W_BYTES;
constexpr int SC0_OFF = EARLY_OFF + 7168, SC1_OFF = R_OFF + 2 * 7168;
constexpr int BAR_OFF = SC_OFF + 16 * 448;
constexpr int TC_OFF = BAR_OFF + 576;
constexpr int SMEM_BYTES = BAR_OFF + 896;
constexpr unsigned READY = MT * 7;
constexpr int UM = 22;

__device__ __align__(1024) uint8_t g_wimg[(size_t)NT * KC * W_BYTES];
__device__ unsigned g_flag[NT * 32];

template <int NR>
__device__ __forceinline__ void store_cols(const float (&acc)[NR], int j0, int j1, uint8_t* p) {
#pragma unroll
    for (int j = j0; j < j1; j++) {
        const int i = 16 * j;
        stg128(p + j * 64, pack_bf16(acc[i], acc[i + 1]), pack_bf16(acc[i + 4], acc[i + 5]), pack_bf16(acc[i + 8], acc[i + 9]), pack_bf16(acc[i + 12], acc[i + 13]));
        stg128(p + j * 64 + 8 * N_ * 2, pack_bf16(acc[i + 2], acc[i + 3]), pack_bf16(acc[i + 6], acc[i + 7]), pack_bf16(acc[i + 10], acc[i + 11]), pack_bf16(acc[i + 14], acc[i + 15]));
    }
}

__host__ __device__ constexpr int slab_at(int u) { return u == 0 ? 2 : (u >= 2 && u <= 5) ? u + 1
        : SS == 0 ? (u == 7 ? 7 : (u >= 9 && u <= 16) ? u - 1 : -1)
        : SS == 1 ? (u == 6 ? 7 : (u >= 9 && u <= 16) ? u - 1 : -1)
        : SS == 2 ? (u == 7 ? 7 : (u >= 8 && u <= 15) ? u : -1)
        : (u == 6 ? 7 : (u >= 8 && u <= 15) ? u : -1); }
__host__ __device__ constexpr int wload_at(int u) {
    return u == 2 ? 2 : u == 4 ? 3 : u == W4U ? 4 : u == 20 ? 15 : u == 18 ? 11 : u == 19 ? 12 : u == 21 ? 13 : u == 7 ? 5
        : WS == 0 ? ((u >= 9 && u <= 17 && (u & 1)) ? (u + 3) / 2 : -1)
        : (u == 10 ? 6 : u == 12 ? 7 : u == 14 ? 8 : u == 15 ? 9 : u == 17 ? 10 : -1);
}
__host__ __device__ constexpr int wload_count(int u) { int n = 0; for (int i = 0; i < u; i++) n += wload_at(i) >= 0; return n; }
__host__ __device__ constexpr int tail_chunk(int j) { return j == 3 ? 15 : j == 4 ? 14 : 11 + j; }
__host__ __device__ constexpr int wbuf(int c) { return c == 15 ? 4 : c & 3; }

__global__ void __cluster_dims__(2, 1, 1) __launch_bounds__(256, 1)
nf4_gemm_kernel(const __nv_bfloat16* __restrict__ cb, const __nv_bfloat16* __restrict__ absmax, uint8_t* __restrict__ wimg,
                unsigned* __restrict__ gflags, uint8_t* __restrict__ out, const unsigned zero, const __grid_constant__ CUtensorMap tmx,
                const __grid_constant__ CUtensorMap tmx64, const __grid_constant__ CUtensorMap tmq, const __grid_constant__ CUtensorMap tmq7,
                const __grid_constant__ CUtensorMap tmq1, const __grid_constant__ CUtensorMap tms) {
    extern __shared__ __align__(1024) uint8_t smem[];
    uint4 c0, c1;
    asm volatile("ld.global.nc.v4.u32 {%0, %1, %2, %3}, [%8];\nld.global.nc.v4.u32 {%4, %5, %6, %7}, [%8 + 16];"
                 : "=r"(c0.x), "=r"(c0.y), "=r"(c0.z), "=r"(c0.w), "=r"(c1.x), "=r"(c1.y), "=r"(c1.z), "=r"(c1.w) : "l"(cb));
    const uint32_t sbase = smem_u32(smem);
    const int rank = blockIdx.x & 1;
    const int mt = (blockIdx.x >> 5) * 2 + rank, nt = (blockIdx.x >> 1) & 15;
    const int warp = __shfl_sync(~0u, (int)(threadIdx.x >> 5), 0);
    const int wg = warp >> 2, wj = warp & 3;
    const int lane = threadIdx.x & 31;
    const uint32_t bars = sbase + BAR_OFF;
    const uint32_t snap = bars;
    const uint32_t xfull = bars + 64 + wg * 40;
    const uint32_t wfull = bars + 144;
    const uint32_t wempty = bars + 184;
    const uint32_t ringfull = bars + 216;
    const uint32_t rawbar = bars + 440;
    const uint32_t earlybar = bars + 472;
    const uint32_t wown = bars + 488;
    const uint32_t wlast = bars + 504;
    const uint32_t sc1bar = earlybar + 8;
    const uint32_t stored = bars + 248;
    const uint32_t xbase = sbase + X_OFF + wg * 40960, wbase = sbase + W_OFF, rbase = sbase + R_OFF;
    const int xrow = mt * BM + wg * 128 + wj * 16;
    const uint8_t* wsrc = wimg + (size_t)nt * KC * W_BYTES;
    unsigned* flags = gflags + nt * 32;
    TS_INIT();

    auto load_slab7 = [&](int c, uint32_t extra = 0) {
        mbar_expect_tx(ringfull + 8 * (c & 3), 7168 + extra);
        tma_load_3d(rbase + (c & 3) * 7168, &tmq7, 0, c * BK + mt * 8, nt * 7, ringfull + 8 * (c & 3));
    };
    auto load_x = [&](int u, int cs = -1, uint32_t bytes = 2048) {
        const int c = u < UM ? u >> 1 : tail_chunk((u - UM) % 5), b = u < UM ? u & 1 : (u - UM) / 5;
        mbar_expect_tx(xfull + 8 * (u % 5), bytes);
        tma_load_2d(xbase + (u % 5) * 8192 + wj * 2048, &tmx, c * BK, xrow + b * 64, xfull + 8 * (u % 5));
        if (cs >= 0) tma_load_2d(rbase + (cs & 3) * 7168 + warp * 1024, &tmq1, nt * BN + warp * 32, cs * BK + mt * 8, xfull + 8 * (u % 5));
    };
    auto load_x64 = [&](int g, int u) {
        const uint32_t bar = bars + 64 + g * 40 + 8 * u;
        mbar_arrive_n(bar, 3);
        mbar_expect_tx(bar, 8192);
        tma_load_2d(sbase + X_OFF + g * 40960 + u * 8192, &tmx64, (u >> 1) * BK, mt * BM + g * 128 + (u & 1) * 64, bar);
    };
    auto load_raw = [&](int c, int p, uint32_t extra) {
        mbar_expect_tx(rawbar + 16 * c + 8 * p, 14336 + extra);
        tma_load_3d(rbase - c * W_BYTES + p * 14336, &tmq, 0, c * BK + rank * 32 + p * 16, nt * 7, rawbar + 16 * c + 8 * p);
    };
    const uint32_t early = sbase + EARLY_OFF;
    auto prefetch = [&](int cs, int cx) {
        if (cx < KC) tma_prefetch_2d(&tmx, cx * BK, mt * BM + nt * 16);
        if (cs < KC) tma_prefetch_3d(&tmq7, 0, cs * BK + mt * 8, nt * 7);
    };
    if (warp == 7) {
        if (elect()) {
            mbar_init(rawbar, 1); mbar_init(rawbar + 8, 1); mbar_init(earlybar, 1);
            fence_async_smem();
            TD(32);
            load_raw(0, 0, 448);
            TD(33);
            bulk_load(sbase + SC0_OFF, absmax + nt * BN, 448, rawbar);
            load_raw(0, 1, 0);
            mbar_expect_tx(earlybar, 7168 + 448);
            if (ORD == 0) {
                tma_load_3d(early, &tmq7, 0, 2 * BK + mt * 8, nt * 7, earlybar);
                bulk_load(sbase + SC0_OFF + 448, absmax + 2 * N_ + nt * BN, 448, earlybar);
            }
            TD(34);
            mbar_init(bars + 64, 4); mbar_init(bars + 72, 4); mbar_init(bars + 104, 4); mbar_init(bars + 112, 4);
            mbar_init(rawbar + 16, 1); mbar_init(rawbar + 24, 1); mbar_init(sc1bar, 1);
            asm volatile("fence.mbarrier_init.release.cluster;" ::: "memory");
            fence_async_smem();
        }
        __syncwarp();
    } else if (warp >= 5) {
        if (elect()) {
            if (warp == 6) {
#pragma unroll
                for (int s = 0; s < 5; s++) mbar_init(wfull + 8 * s, 1);
#pragma unroll
                for (int s = 0; s < 4; s++) mbar_init(wempty + 8 * s, 16);
                mbar_init(wown, 7); mbar_init(wown + 8, 7); mbar_init(stored, 224); mbar_init(stored + 8, 224); mbar_init(stored + 16, 224); mbar_init(stored + 24, 224);
                mbar_init(wlast, 1);
                mbar_expect_tx(wfull, W_BYTES / 2); mbar_expect_tx(wfull + 8, W_BYTES / 4); mbar_expect_tx(wlast, W_BYTES / 4);
            }
            if (warp == 5) {
#pragma unroll
                for (int s = 0; s < 10; s++) if (s % 5 >= 2) mbar_init(bars + 64 + 8 * s, 4);
#pragma unroll
                for (int s = 0; s < 4; s++) mbar_init(ringfull + 8 * s, 1);
            }
            asm volatile("fence.mbarrier_init.release.cluster;" ::: "memory");
            fence_async_smem();
        }
        __syncwarp();
    }
    cluster_arrive();
    if (warp == 7) {
        if (elect()) {
            TD(35);
            load_x64(0, 0); load_x64(0, 1);
            if (ORD == 1) {
                tma_load_3d(early, &tmq7, 0, 2 * BK + mt * 8, nt * 7, earlybar);
                bulk_load(sbase + SC0_OFF + 448, absmax + 2 * N_ + nt * BN, 448, earlybar);
            }
            load_x64(1, 0); load_x64(1, 1);
            TD(36);
            if (R1E) load_raw(1, 0, F1A ? 0 : 448);
            if (PF1) tma_prefetch_3d(&tmq7, 0, BK + rank * 32 + (mt >> 1) * 8, nt * 7);
            asm volatile("cp.async.bulk.prefetch.L2.global [%0], 448;" ::"l"(absmax + N_ + nt * BN) : "memory");
            TD(37);
        }
        __syncwarp();
    }
    Lut lut = {};
    if (warp < 7) {
        lut.lo[0] = __byte_perm(c0.x, c0.y, 0x6420); lut.hi[0] = __byte_perm(c0.x, c0.y, 0x7531);
        lut.lo[1] = __byte_perm(c0.z, c0.w, 0x6420); lut.hi[1] = __byte_perm(c0.z, c0.w, 0x7531);
        lut.lo[2] = __byte_perm(c1.x, c1.y, 0x6420); lut.hi[2] = __byte_perm(c1.x, c1.y, 0x7531);
        lut.lo[3] = __byte_perm(c1.z, c1.w, 0x6420); lut.hi[3] = __byte_perm(c1.z, c1.w, 0x7531);
    }
    cluster_wait();
    TC(1);
    if (warp == 7) {
        mbar_wait(rawbar, 0);
        TD(38);
        if (!R1E && elect()) load_raw(1, 0, F1A ? 0 : 448);
        __syncwarp();
        mbar_wait(rawbar + 8, 0);
        TD(39);
        if (elect()) prefetch(PF3 == 0 ? 3 : 99, 1);
        __syncwarp();
        mbar_wait(wown, 0);
        TD(40);
        if (elect()) {
            if (F1A) mbar_expect_tx(sc1bar, 448);
            bulk_load(sbase + SC1_OFF, absmax + N_ + nt * BN, 448, F1A ? sc1bar : rawbar + 16);
            load_raw(1, 1, 0);
            if (PF3 == 1) prefetch(3, 99);
        }
        __syncwarp();
    }
    const uint32_t rlane = (lane & 7) * 128 + ((((lane >> 3) * 2) ^ (lane & 7)) << 4);
    const uint32_t wlane = warp * 1024 + (lane & 7) * 16 + (lane >> 3) * 4;
    const uint32_t ssrc = sbase + warp * 64 + (lane >> 3) * 16;
    uint8_t* gdst = wimg + (size_t)nt * KC * W_BYTES + (mt >> 1) * 7168 + (mt & 1) * 128 + wlane;
    auto scales = [&](int c) { return lds128(ssrc + (c ? SC1_OFF : SC0_OFF)); };
    auto fetch = [&](uint32_t a, uint32_t& p1, uint32_t& p2) {
        a += warp * 2048;
        const uint4 v0 = lds128(a + rlane), v1 = lds128(a + (rlane ^ 16)), v2 = lds128(a + rlane + 1024), v3 = lds128(a + (rlane ^ 16) + 1024);
        pack16(v0, v1, v2, v3, p1, p2);
    };
    auto sts4 = [&](uint32_t d, const uint4& w) { sts32(d, w.x); sts32(d + 256, w.y); sts32(d + 512, w.z); sts32(d + 768, w.w); };
    auto put_local = [&](int c, int p, uint32_t p1, uint32_t p2) {
        TD(33 + 6 * (2 * c + p));
        const uint4 sc = scales(c);
        const uint32_t d = wbase + c * W_BYTES + rank * 14336 + p * 7168;
        sts4(d + wlane, dequant16<0>(p1, p2, sc, lut));
        sts4(d + wlane + 128, dequant16<1>(p1, p2, sc, lut));
        TD(34 + 6 * (2 * c + p));
        fence_async_smem();
        __syncwarp();
        TD(35 + 6 * (2 * c + p));
        if (elect()) {
            if (p) mbar_arrive(wown + 8 * c);
            if (c == 0 || p == 0) copy_to_peer(d + warp * 1024, 1024, wfull + 8 * c, rank ^ 1);
        }
        __syncwarp();
        TD(36 + 6 * (2 * c + p));
    };
    uint32_t slabsrc = (warp < 7 ? warp * 1024 + rlane : 0) + sbase;
    uint32_t scsrc = warp < 7 ? ssrc : sbase + (lane >> 3) * 16;
    uint8_t *gkeep = gdst, *gprobe = warp < 7 ? gdst + (lane >> 3) * 252 : (uint8_t*)flags + (lane >> 3) * 16;
    auto store_slab = [&](int c, uint32_t p, const uint4& sc) {
        const uint4 w = dequant8p(p, sc, lut);
        uint8_t* g = gkeep + (size_t)c * W_BYTES;
        stg32(g, w.x); stg32(g + 256, w.y); stg32(g + 512, w.z); stg32(g + 768, w.w);
        probe_l2(scsrc + SC_OFF + 448 * 2, gprobe + (size_t)c * W_BYTES, (lane & 7) == 0);
    };
    auto convert_slab = [&](int c) {
        const uint32_t o = c == 2 ? EARLY_OFF : R_OFF + (c & 3) * 7168;
        const uint4 q0 = lds128(slabsrc + o), q1 = lds128((slabsrc ^ 16) + o);
        store_slab(c, pack8x(q0, q1), lds128(scsrc + (c == 2 ? SC0_OFF + 448 : SC_OFF + 448 * c)));
    };
    uint32_t p1, p2;
    if (warp < 7) {
        mbar_wait(rawbar, 0);
        TC(5); TD(32);
        fetch(rbase, p1, p2);
        put_local(0, 0, p1, p2);
        TC(7);
        mbar_wait(rawbar + 8, 0);
        TD(38);
        fetch(rbase + 14336, p1, p2);
        put_local(0, 1, p1, p2);
        TC(6);
        mbar_wait(earlybar, 0);
        TD(56);
        convert_slab(2);
        probe_arrive(stored);
        if (F1A) {
            TD(57);
            mbar_wait(rawbar + 16, 0);
            TD(58);
            fetch(wbase + 3 * W_BYTES, p1, p2);
        }
    }
    TC(2);
    auto take_sample = [&]() { probe_l2(scsrc + BAR_OFF, gprobe, (lane & 7) == 0); };
    auto load_w = [&](int c, int sample) {
        if (c <= 4) TD(44 + 6 * (c - 2));
        if (sample >= 0) { probe_wait<0>(); __syncwarp(); }
        if (c <= 4) TD(45 + 6 * (c - 2));
        poll_ge(flags + c, sample >= -1 ? lds32(snap + 4 * c) : 0, READY);
        if (c <= 4) TD(46 + 6 * (c - 2));
        asm volatile("fence.acquire.gpu;" ::: "memory");
        asm volatile("fence.proxy.async.global;" ::: "memory");
        if (c >= 4 && c < 15) mbar_wait(wempty + 8 * (c & 3), ((c >> 2) - 1) & 1);
        if (elect()) {
            mbar_expect_tx(wfull + 8 * wbuf(c), W_BYTES);
            bulk_load_mc(wbase + wbuf(c) * W_BYTES + rank * (W_BYTES / 2), wsrc + (size_t)c * W_BYTES + rank * (W_BYTES / 2), W_BYTES / 2, wfull + 8 * wbuf(c));
        }
        __syncwarp();
        if (c <= 4) TD(47 + 6 * (c - 2));
    };

    float acc0[112], acc1[112];
    const uint32_t descA = ((xbase & 0x3FFFF) >> 4) | (1u << 16), descB = ((wbase & 0x3FFFF) >> 4) | ((128u >> 4) << 16);
    static_for<0, UM>([&](auto U) __attribute__((always_inline)) {
        constexpr int u = U.value, kc = u >> 1;
        uint32_t da = descA, db = descB;
        asm volatile("" : "+r"(da), "+r"(db));
        db += (kc & 3) * (W_BYTES >> 4);
        uint4 q0, q1, sc;
        const int c = slab_at(u);
        auto early_loads = [&]() {
            q0 = lds128(slabsrc + R_OFF + (c & 3) * 7168); q1 = lds128((slabsrc ^ 16) + R_OFF + (c & 3) * 7168);
            sc = lds128(scsrc + SC_OFF + 448 * c);
        };
        if (u < 4) {
            if (u == 0) mbar_wait3(xfull, 0, xfull + 8, 0, wown, 0);
            if (u == 1) mbar_wait(wfull, 0);
            if (u == 2) mbar_wait4(xfull + 16, 0, xfull + 24, 0, wown + 8, 0, ringfull + 24, 0);
            if (u == 3) mbar_wait2(wfull + 8, 0, ringfull, 0);
            TM(8 + 3 * u);
            if (u >= 2) early_loads();
            const int h = rank ^ (u & 1);
            da += kc * 1024 + h * 4; db += h * (14336 >> 4);
            wgmma_fence();
            if (u == 0) { wgmma_ss<0>(acc0, da, db); wgmma_ss<0>(acc1, da + 512, db); }
            else { wgmma_ss<1>(acc0, da, db); wgmma_ss<1>(acc1, da + 512, db); }
            if (u < 3) { wgmma_ss<1>(acc0, da + 2, db + (7168 >> 4)); wgmma_ss<1>(acc1, da + 514, db + (7168 >> 4)); }
        } else {
            da += (u % 5) * 512;
            if (c >= 0 && c < 8 && !LATERING) {
                if (u & 1) mbar_wait2(xfull + 8 * (u % 5), (u / 5) & 1, ringfull + 8 * (c & 3), c == 7);
                else mbar_wait3(xfull + 8 * (u % 5), (u / 5) & 1, wfull + 8 * (kc & 3), (kc >> 2) & 1, ringfull + 8 * (c & 3), c == 7);
            } else {
                if (u & 1) mbar_wait(xfull + 8 * (u % 5), (u / 5) & 1);
                else mbar_wait2(xfull + 8 * (u % 5), (u / 5) & 1, wfull + 8 * (kc & 3), (kc >> 2) & 1);
            }
            if (warp == 7 && u >= 5 && u <= LATES && wload_at(u) >= 0) take_sample();
            if (c >= (LATERING ? 8 : 0)) early_loads();
            TM(8 + 3 * u);
            wgmma_fence();
#pragma unroll
            for (int ks = 0; ks < 4; ks++) {
                if (u & 1) wgmma_ss<1>(acc1, da + ks * 2, db + ks * (7168 >> 4));
                else wgmma_ss<1>(acc0, da + ks * 2, db + ks * (7168 >> 4));
            }
        }
        wgmma_commit();
        if (u >= 4) {
            wgmma_wait<1>();
            TM(9 + 3 * u);
        }
        if (warp < 7) {
            if (u < 2) {
                if (F1A && u == 0) mbar_wait(sc1bar, 0);
                else {
                    mbar_wait(rawbar + 16 + 8 * u, 0);
                    TM(9 + 3 * u);
                    fetch(wbase + 3 * W_BYTES + u * 14336, p1, p2);
                }
                put_local(1, u, p1, p2);
            } else if (u < 4) {
                store_slab(c, pack8x(q0, q1), sc);
                probe_arrive(stored + 8 * (c - 2));
                TM(9 + 3 * u);
            } else {
                const int cn = slab_at(u + 4);
                const int cp = u <= 6 ? -1 : slab_at(u - 2);
                uint32_t p = 0;
                if (LATERING && c >= 0 && c < 8) { mbar_wait(ringfull + 8 * (c & 3), c == 7); early_loads(); }
                if (c >= 0) p = pack8x(q0, q1);
                if (cp >= 0) { if (slab_at(u - 1) >= 0) probe_wait<1>(); else probe_wait<0>(); __syncwarp(); }
                if (elect()) {
                    if (u == 4) load_x(7);
                    if (u == 5) load_x(8, slab_at(8), slab_at(8) >= 0 ? 3072 : 2048);
                    if (u > 4) load_x(u + 4, cn, cn >= 0 ? after(3072, p, zero) : 2048);
                    if (!(u & 1)) mbar_arrive_both(wempty + 8 * ((kc - 1) & 3));
                    if (cp >= 0) red_add(flags + cp, 1);
                }
                __syncwarp();
                if (c >= 0) store_slab(c, p, sc);
                if (u == 4) probe_arrive(stored + 24);
            }
        } else if (u == 2) {
            if (W2U == 2) load_w(2, 0);
            if (elect()) copy_to_peer(wbase + W_BYTES + rank * 14336 + 7168, 7168, wlast, rank ^ 1);
            __syncwarp();
        }
        if (u == 2) {
            wgmma_wait<1>();
            if (elect()) { load_x(5); mbar_arrive_both(wempty); }
            __syncwarp();
        }
        if (u == 3) {
            if (warp == 7) {
                mbar_wait(stored + 8, 0);
                TM(9 + 3 * u);
                if (elect()) red_add(flags + 3, 7);
                __syncwarp();
            }
            mbar_wait(wlast, 0);
            wgmma_fence();
            wgmma_ss<1>(acc0, da + 2, db + (7168 >> 4)); wgmma_ss<1>(acc1, da + 514, db + (7168 >> 4));
            wgmma_commit();
            if (elect()) load_x(6);
            gkeep = (uint8_t*)__shfl_sync(~0u, (unsigned long long)gkeep, lane);
            gprobe = (uint8_t*)__shfl_sync(~0u, (unsigned long long)gprobe, lane);
            slabsrc = __shfl_sync(~0u, slabsrc, lane);
            scsrc = __shfl_sync(~0u, scsrc, lane);
        }
        if (warp == 7) {
            if (u >= 4) {
                if (elect()) {
                    if (u == 4) load_x(7);
                    if (u == 5) load_x(8);
                    if (u > 4) load_x(u + 4);
                    if (!(u & 1)) mbar_arrive_both(wempty + 8 * ((kc - 1) & 3));
                }
                __syncwarp();
            }
            if (u == 0) {
                if (elect()) { load_x64(0, 2); load_x64(0, 3); }
                __syncwarp();
                mbar_wait(stored, 0);
                TM(9);
                if (elect()) {
                    red_add(flags + 2, 7);
                    load_x64(1, 2); load_x64(1, 3);
                    load_slab7(3, 14 * 448);
                    tma_load_2d(sbase + SC_OFF + 896, &tms, nt * BN, 2, ringfull + 24);
                    prefetch(PF4 ? 4 : 99, 2);
                }
                __syncwarp();
            } else if (u == 1) {
                if (DLY2) delay(DLY2);
                take_sample();
                if (elect()) { load_slab7(4); load_x64(0, 4); load_x64(1, 4); prefetch(99, 3); }
                __syncwarp();
                if (W2U == 1) load_w(2, 0);
            } else if (u == 2) {
                if (elect()) { load_slab7(5); if (PFV == 0) { load_slab7(6); prefetch(8, 5); } else if (PFV < 3) prefetch(6, 4); else if (PFX) prefetch(99, 4); }
                __syncwarp();
            } else if (u == 3) {
                if (elect()) { if (PFV == 0) prefetch(99, 6); else { load_slab7(6); if (PFV < 3) prefetch(7, 5); else if (PFX) prefetch(99, 5); } }
                __syncwarp();
                if (DLY3) delay(DLY3);
            } else {
                if (u == 4 || u == 5) {
                    mbar_wait(stored + 8 * (u - 2), 0);
                    if (elect()) red_add(flags + u, 7);
                    __syncwarp();
                }
                if (u + 2 < KC) {
                    if (elect()) { if (u == S7U) load_slab7(7); if (PFV == 0) prefetch(u + 5, u + 3); else if (PFV < 3) prefetch(u + 4, u + 2); else if (PFX) prefetch(99, u + 2); }
                    __syncwarp();
                }
            }
            if (u > 2 && wload_at(u) >= 0) load_w(wload_at(u), wload_count(u));
            if (u > 1 && u + 1 < UM && wload_at(u + 1) >= 0 && !(u + 1 >= 5 && u + 1 <= LATES)) take_sample();
        }
        TM(10 + 3 * u);
    });
    uint32_t tA = descA, tB = descB;
    asm volatile("" : "+r"(tA), "+r"(tB));
    if (wg == 1) {
        wgmma_wait<0>();
        if (elect()) { load_x(UM + 4); mbar_arrive_both(wempty + 16); }
        __syncwarp();
        if (warp == 7) load_w(14, -1);
    if (warp == 7 && lane == 0) {
        if (atomicAdd(flags + 16, 1) == MT - 1) {
#pragma unroll
            for (int c = 0; c <= 16; c++) flags[c] = 0;
        }
    }
    __syncwarp();
        bar_sync<256>(1);
    }
    TC(74);
#pragma unroll
    for (int j = 0; j < 5; j++) {
        const int c = tail_chunk(j), v = UM + j;
        mbar_wait2(xfull + 8 * (v % 5), (v / 5) & 1, wfull + 8 * wbuf(c), c == 15 ? 0 : (c >> 2) & 1);
        wgmma_fence();
#pragma unroll
        for (int ks = 0; ks < 4; ks++) wgmma_ss<1>(acc0, tA + (v % 5) * 512 + ks * 2, tB + wbuf(c) * (W_BYTES >> 4) + ks * (7168 >> 4));
        wgmma_commit();
        if (j == 4) bar_arrive<256>(1 + wg);
        wgmma_wait<1>();
        if (j > 0 || wg == 0) {
            if (elect()) { load_x(v + 4); if (j == 0) mbar_arrive_both(wempty + 16); }
            __syncwarp();
        }
    }
    wgmma_wait<0>();
    TC(75);
    if (elect()) load_x(UM + 9);
    __syncwarp();
    uint8_t* optr = out + (size_t)(xrow + (lane >> 2)) * (N_ * 2) + nt * (BN * 2) + (lane & 3) * 16;
#define NA 4
#define NB 2
#define LEFT0 4
#define LEFT1 1
    constexpr int NC = 7 - NA - NB;
    float pa[16 * NA], pb[16 * NB], pc[16 * NC];
#pragma unroll
    for (int i = 0; i < 16 * NA; i++) asm volatile("mov.b32 %0, %1;" : "=f"(pa[i]) : "f"(acc1[i]));
#pragma unroll
    for (int i = 0; i < 16 * NB; i++) asm volatile("mov.b32 %0, %1;" : "=f"(pb[i]) : "f"(acc1[16 * NA + i]));
#pragma unroll
    for (int i = 0; i < 16 * NC; i++) asm volatile("mov.b32 %0, %1;" : "=f"(pc[i]) : "f"(acc1[16 * (NA + NB) + i]));
    uint4 af[16];
    uint32_t pk[56];
#pragma unroll
    for (int i = 0; i < 56; i++) pk[i] = pack_bf16(acc0[2 * i], acc0[2 * i + 1]);
    auto store_pk = [&](int h) {
        const int i = 8 * (h >> 1) + (h & 1);
        stg128(optr + (h >> 1) * 64 + (h & 1) * (8 * N_ * 2), pk[i], pk[i + 2], pk[i + 4], pk[i + 6]);
    };
    {
        const uint32_t alane = xbase + wj * 2048 + (lane & 15) * 128 + (((lane >> 4) ^ (lane & 7)) << 4);
        store_pk(0); store_pk(1);
#pragma unroll
        for (int j = 0; j < 4; j++) {
            const int v = UM + 5 + j;
            mbar_wait(xfull + 8 * (v % 5), (v / 5) & 1);
#pragma unroll
            for (int ks = 0; ks < 4; ks++) af[4 * j + ks] = ldmatrix_x4((alane ^ (ks * 32)) + (v % 5) * 8192);
#pragma unroll
            for (int h = 2 + j * (12 - 2 * LEFT0) / 4; h < 2 + (j + 1) * (12 - 2 * LEFT0) / 4; h++) store_pk(h);
        }
    }
    if (wg == 0) {
#pragma unroll
        for (int h = 14 - 2 * LEFT0; h < 14; h++) store_pk(h);
    }
    mbar_wait(xfull + 8 * ((UM + 9) % 5), ((UM + 9) / 5) & 1);
    TC(76);
    auto piece = [&](auto& d, int cb) {
        wgmma_fence();
#pragma unroll
        for (int j = 0; j < 5; j++)
#pragma unroll
            for (int ks = 0; ks < 4; ks++) {
                const uint32_t db = tB + wbuf(tail_chunk(j)) * (W_BYTES >> 4) + ks * (7168 >> 4) + cb * 64;
                if (j < 4) wgmma_rs(d, af[4 * j + ks], db);
                else wgmma_ss<1>(d, tA + ((UM + 9) % 5) * 512 + ks * 2, db);
            }
        wgmma_commit();
    };
    bar_sync<256>(2 + wg);
    TC(77);
    piece(pa, 0);
    bar_arrive<256>(3 + wg);
    if (wg == 1) {
#pragma unroll
        for (int h = 14 - 2 * LEFT0; h < 14; h++) store_pk(h);
    }
    wgmma_wait<0>();
    TC(78);
    optr += 64 * N_ * 2;
    store_cols(pa, 0, NA - LEFT1, optr);
    if (wg == 0) store_cols(pa, NA - LEFT1, NA, optr);
    TC(79);
    bar_sync<256>(4 + wg);
    piece(pb, NA);
    bar_arrive<256>(5 + wg);
    if (wg == 1) store_cols(pa, NA - LEFT1, NA, optr);
    wgmma_wait<0>();
    TC(2);
    if (wg == 0) store_cols(pb, 0, NB, optr + NA * 64);
    bar_sync<256>(6 + wg);
    piece(pc, NA + NB);
    if (wg == 0) bar_arrive<256>(7);
    else store_cols(pb, 0, NB, optr + NA * 64);
    cluster_arrive();
    wgmma_wait<0>();
    TC(3);
    store_cols(pc, 0, NC, optr + (NA + NB) * 64);
    TC(4);
    TS_DUMP();
    cluster_wait();
}

typedef CUresult (*EncodeFn)(CUtensorMap*, CUtensorMapDataType, cuuint32_t, void*, const cuuint64_t*, const cuuint64_t*,
                             const cuuint32_t*, const cuuint32_t*, CUtensorMapInterleave, CUtensorMapSwizzle,
                             CUtensorMapL2promotion, CUtensorMapFloatOOBfill);

extern "C" void kernel_launch(void* const* d_in, const int* in_sizes, int n_in, void* d_out, int out_size) {
    const __nv_bfloat16* x = (const __nv_bfloat16*)d_in[0];
    const int* qw = (const int*)d_in[1];
    const __nv_bfloat16* cb = (const __nv_bfloat16*)d_in[2];
    const __nv_bfloat16* absmax = (const __nv_bfloat16*)d_in[3];
    static EncodeFn encode = nullptr;
    static void *wimg = nullptr, *gflags = nullptr;
    if (!encode) {
        cudaGetSymbolAddress(&wimg, g_wimg);
        cudaGetSymbolAddress(&gflags, g_flag);
        void* fn = nullptr;
        cudaDriverEntryPointQueryResult qr;
        cudaGetDriverEntryPoint("cuTensorMapEncodeTiled", &fn, cudaEnableDefault, &qr);
        encode = (EncodeFn)fn;
        cudaFuncSetAttribute(nf4_gemm_kernel, cudaFuncAttributeMaxDynamicSharedMemorySize, SMEM_BYTES);
    }
    CUtensorMap tmx, tmx64, tmq, tmq7, tmq1, tms;
    const cuuint32_t es[3] = {1, 1, 1};
    {
        cuuint64_t dims[2] = {(cuuint64_t)K_, (cuuint64_t)M_};
        cuuint64_t strides[1] = {(cuuint64_t)K_ * 2};
        cuuint32_t box[2] = {64, 16};
        encode(&tmx, CU_TENSOR_MAP_DATA_TYPE_BFLOAT16, 2, (void*)x, dims, strides, box, es, CU_TENSOR_MAP_INTERLEAVE_NONE,
               CU_TENSOR_MAP_SWIZZLE_128B, CU_TENSOR_MAP_L2_PROMOTION_L2_128B, CU_TENSOR_MAP_FLOAT_OOB_FILL_NONE);
        box[1] = 64;
        encode(&tmx64, CU_TENSOR_MAP_DATA_TYPE_BFLOAT16, 2, (void*)x, dims, strides, box, es, CU_TENSOR_MAP_INTERLEAVE_NONE,
               CU_TENSOR_MAP_SWIZZLE_128B, CU_TENSOR_MAP_L2_PROMOTION_L2_128B, CU_TENSOR_MAP_FLOAT_OOB_FILL_NONE);
    }
    {
        cuuint64_t dims[3] = {32, (cuuint64_t)K_, (cuuint64_t)(N_ / 32)};
        cuuint64_t strides[2] = {(cuuint64_t)N_ * 4, 128};
        cuuint32_t box[3] = {32, 16, 7};
        encode(&tmq, CU_TENSOR_MAP_DATA_TYPE_INT32, 3, (void*)qw, dims, strides, box, es, CU_TENSOR_MAP_INTERLEAVE_NONE,
               CU_TENSOR_MAP_SWIZZLE_128B, CU_TENSOR_MAP_L2_PROMOTION_L2_128B, CU_TENSOR_MAP_FLOAT_OOB_FILL_NONE);
        box[1] = 8;
        encode(&tmq7, CU_TENSOR_MAP_DATA_TYPE_INT32, 3, (void*)qw, dims, strides, box, es, CU_TENSOR_MAP_INTERLEAVE_NONE,
               CU_TENSOR_MAP_SWIZZLE_128B, CU_TENSOR_MAP_L2_PROMOTION_L2_128B, CU_TENSOR_MAP_FLOAT_OOB_FILL_NONE);
    }
    {
        cuuint64_t dims[2] = {(cuuint64_t)N_, (cuuint64_t)K_};
        cuuint64_t strides[1] = {(cuuint64_t)N_ * 4};
        cuuint32_t box[2] = {32, 8};
        encode(&tmq1, CU_TENSOR_MAP_DATA_TYPE_INT32, 2, (void*)qw, dims, strides, box, es, CU_TENSOR_MAP_INTERLEAVE_NONE,
               CU_TENSOR_MAP_SWIZZLE_128B, CU_TENSOR_MAP_L2_PROMOTION_L2_128B, CU_TENSOR_MAP_FLOAT_OOB_FILL_NONE);
    }
    {
        cuuint64_t dims[2] = {(cuuint64_t)N_, (cuuint64_t)KC};
        cuuint64_t strides[1] = {(cuuint64_t)N_ * 2};
        cuuint32_t box[2] = {BN, KC - 2};
        encode(&tms, CU_TENSOR_MAP_DATA_TYPE_BFLOAT16, 2, (void*)absmax, dims, strides, box, es, CU_TENSOR_MAP_INTERLEAVE_NONE,
               CU_TENSOR_MAP_SWIZZLE_NONE, CU_TENSOR_MAP_L2_PROMOTION_NONE, CU_TENSOR_MAP_FLOAT_OOB_FILL_NONE);
    }
    nf4_gemm_kernel<<<128, 256, SMEM_BYTES>>>(cb, absmax, (uint8_t*)wimg, (unsigned*)gflags, (uint8_t*)d_out, 0u, tmx, tmx64, tmq, tmq7, tmq1, tms);
}
```

```cpp
#include <cuda_runtime.h>
#include <cuda_bf16.h>
#include <cuda.h>
#include <stdint.h>

constexpr int M_ = 2048, K_ = 1024, N_ = 3584;
constexpr int BM = 256, BN = 224, BK = 64;
constexpr int KC = K_ / BK;

#define TSW(w, i)
#define TS_INIT()
#define TS_DUMP()

#define TC(i)
#define TS_FIRST()
#define TG(i)
__device__ __forceinline__ uint32_t smem_u32(const void* p) { return (uint32_t)__cvta_generic_to_shared(p); }
__device__ __forceinline__ bool elect() {
    uint32_t ok;
    asm volatile("{\n.reg .pred p;\nelect.sync _|p, 0xffffffff;\nselp.u32 %0, 1, 0, p;\n}\n" : "=r"(ok));
    return ok != 0;
}
__device__ __forceinline__ void mbar_init(uint32_t bar, uint32_t cnt) { asm volatile("mbarrier.init.shared::cta.b64 [%0], %1;" ::"r"(bar), "r"(cnt) : "memory"); }
__device__ __forceinline__ void mbar_expect_tx(uint32_t bar, uint32_t bytes) { asm volatile("mbarrier.arrive.expect_tx.shared::cta.b64 _, [%0], %1;" ::"r"(bar), "r"(bytes) : "memory"); }
__device__ __forceinline__ void mbar_arrive(uint32_t bar) { asm volatile("mbarrier.arrive.shared::cta.b64 _, [%0];" ::"r"(bar) : "memory"); }
__device__ __forceinline__ void mbar_wait(uint32_t bar, uint32_t parity) {
    asm volatile(
        "{\n.reg .pred p;\n.reg .b32 n;\n"
        "mbarrier.try_wait.parity.shared::cta.b64 p, [%0], %1;\n"
        "@p bra LAB_DONE;\n"
        "mov.b32 n, 0;\n"
        "LAB_WAIT:\n"
        "mbarrier.try_wait.parity.shared::cta.b64 p, [%0], %1;\n"
        "@p bra LAB_DONE;\n"
        "add.u32 n, n, 1;\n"
        "setp.lt.u32 p, n, 0x40000;\n"
        "@p bra LAB_WAIT;\n"
        "trap;\n"
        "LAB_DONE:\n}\n" ::"r"(bar), "r"(parity) : "memory");
}
__device__ __forceinline__ void tma_load_2d(uint32_t dst, const CUtensorMap* tm, int c0, int c1, uint32_t bar) {
    asm volatile("cp.async.bulk.tensor.2d.shared::cluster.global.mbarrier::complete_tx::bytes [%0], [%1, {%2, %3}], [%4];"
                 ::"r"(dst), "l"(tm), "r"(c0), "r"(c1), "r"(bar) : "memory");
}
__device__ __forceinline__ void tma_prefetch_2d(const CUtensorMap* tm, int c0, int c1) {
    asm volatile("cp.async.bulk.prefetch.tensor.2d.L2.global [%0, {%1, %2}];" ::"l"(tm), "r"(c0), "r"(c1) : "memory");
}
__device__ __forceinline__ void bulk_load(uint32_t dst, const void* src, uint32_t bytes, uint32_t bar) {
    asm volatile("cp.async.bulk.shared::cluster.global.mbarrier::complete_tx::bytes [%0], [%1], %2, [%3];"
                 ::"r"(dst), "l"(src), "r"(bytes), "r"(bar) : "memory");
}
__device__ __forceinline__ void tma_store_3d(const CUtensorMap* tm, uint32_t src, int c0, int c1, int c2) {
    asm volatile("cp.async.bulk.tensor.3d.global.shared::cta.bulk_group [%0, {%2, %3, %4}], [%1];"
                 ::"l"(tm), "r"(src), "r"(c0), "r"(c1), "r"(c2) : "memory");
}
__device__ __forceinline__ void mbar_arrive_both(uint32_t bar) {
    asm volatile("{\n.reg .b32 ra;\nmapa.shared::cluster.u32 ra, %0, 0;\nmbarrier.arrive.shared::cluster.b64 _, [ra];\n"
                 "mapa.shared::cluster.u32 ra, %0, 1;\nmbarrier.arrive.shared::cluster.b64 _, [ra];\n}\n" ::"r"(bar) : "memory");
}
__device__ __forceinline__ void cluster_arrive() { asm volatile("barrier.cluster.arrive.relaxed.aligned;" ::: "memory"); }
__device__ __forceinline__ void cluster_wait() { asm volatile("barrier.cluster.wait.acquire.aligned;" ::: "memory"); }
__device__ __forceinline__ uint32_t mapa(uint32_t addr, uint32_t cta) {
    uint32_t r; asm("mapa.shared::cluster.u32 %0, %1, %2;" : "=r"(r) : "r"(addr), "r"(cta)); return r;
}
__device__ __forceinline__ void copy_to_peer(uint32_t addr, uint32_t bytes, uint32_t bar, uint32_t peer) {
    asm volatile("cp.async.bulk.shared::cluster.shared::cta.mbarrier::complete_tx::bytes [%0], [%1], %2, [%3];"
                 ::"r"(mapa(addr, peer)), "r"(addr), "r"(bytes), "r"(mapa(bar, peer)) : "memory");
}
__device__ __forceinline__ void wgmma_fence() { asm volatile("wgmma.fence.sync.aligned;" ::: "memory"); }
__device__ __forceinline__ void wgmma_commit() { asm volatile("wgmma.commit_group.sync.aligned;" ::: "memory"); }
template <int N> __device__ __forceinline__ void wgmma_wait() { asm volatile("wgmma.wait_group.sync.aligned %0;" ::"n"(N) : "memory"); }
__device__ __forceinline__ uint32_t pack_bf16(float lo, float hi) {
    uint32_t r; asm("cvt.rn.bf16x2.f32 %0, %1, %2;" : "=r"(r) : "f"(hi), "f"(lo)); return r;
}
__device__ __forceinline__ void stmatrix_x4(uint32_t addr, uint32_t a, uint32_t b, uint32_t c, uint32_t d) {
    asm volatile("stmatrix.sync.aligned.m8n8.x4.shared.b16 [%0], {%1, %2, %3, %4};" ::"r"(addr), "r"(a), "r"(b), "r"(c), "r"(d) : "memory");
}
__device__ __forceinline__ uint4 lds128(uint32_t a) {
    uint4 v; asm volatile("ld.shared.v4.b32 {%0, %1, %2, %3}, [%4];" : "=r"(v.x), "=r"(v.y), "=r"(v.z), "=r"(v.w) : "r"(a) : "memory"); return v;
}
__device__ __forceinline__ void sts128(uint32_t a, uint4 v) {
    asm volatile("st.shared.v4.b32 [%0], {%1, %2, %3, %4};" ::"r"(a), "r"(v.x), "r"(v.y), "r"(v.z), "r"(v.w) : "memory");
}
template <int NTHR> __device__ __forceinline__ void bar_arrive(int id) { asm volatile("bar.arrive %0, %1;" ::"r"(id), "n"(NTHR) : "memory"); }
template <int NTHR> __device__ __forceinline__ void bar_sync(int id) { asm volatile("bar.sync %0, %1;" ::"r"(id), "n"(NTHR) : "memory"); }
__device__ __forceinline__ uint32_t mul_bf16x2(uint32_t a, uint32_t b) { uint32_t r; asm("mul.rn.bf16x2 %0, %1, %2;" : "=r"(r) : "r"(a), "r"(b)); return r; }
__device__ __forceinline__ uint4 dequant8(const uint4& q0, const uint4& q1, const uint4& sc, uint32_t tab) {
    uint4 r;
    r.x = mul_bf16x2(__byte_perm(__shfl_sync(~0u, tab, q0.x), __shfl_sync(~0u, tab, q0.y), 0x5410), sc.x);
    r.y = mul_bf16x2(__byte_perm(__shfl_sync(~0u, tab, q0.z), __shfl_sync(~0u, tab, q0.w), 0x5410), sc.y);
    r.z = mul_bf16x2(__byte_perm(__shfl_sync(~0u, tab, q1.x), __shfl_sync(~0u, tab, q1.y), 0x5410), sc.z);
    r.w = mul_bf16x2(__byte_perm(__shfl_sync(~0u, tab, q1.z), __shfl_sync(~0u, tab, q1.w), 0x5410), sc.w);
    return r;
}
struct Lut { uint32_t lo[4], hi[4]; };
__device__ __forceinline__ uint32_t prmt(uint32_t a, uint32_t b, uint32_t s) { uint32_t r; asm("prmt.b32 %0, %1, %2, %3;" : "=r"(r) : "r"(a), "r"(b), "r"(s)); return r; }
__device__ __forceinline__ void lookup4(const uint4& q, const Lut& t, uint32_t& w01, uint32_t& w23) {
    uint32_t ab, cd, p;
    asm("mad.lo.u32 %0, %1, 16, %2;" : "=r"(ab) : "r"(q.y), "r"(q.x));
    asm("mad.lo.u32 %0, %1, 16, %2;" : "=r"(cd) : "r"(q.w), "r"(q.z));
    asm("mad.lo.u32 %0, %1, 256, %2;" : "=r"(p) : "r"(cd), "r"(ab));
    const uint32_t sel = ((p >> 1) & 0x4444u) | 0x3210u;
    const uint32_t s7 = p & 0x7777u;
    const uint32_t lo = prmt(prmt(t.lo[0], t.lo[1], p), prmt(t.lo[2], t.lo[3], s7), sel);
    const uint32_t hi = prmt(prmt(t.hi[0], t.hi[1], p), prmt(t.hi[2], t.hi[3], s7), sel);
    w01 = prmt(lo, hi, 0x5140);
    w23 = prmt(lo, hi, 0x7362);
}
__device__ __forceinline__ uint4 dequant8_alu(const uint4& q0, const uint4& q1, const uint4& sc, const Lut& t) {
    uint4 r;
    lookup4(q0, t, r.x, r.y);
    lookup4(q1, t, r.z, r.w);
    r.x = mul_bf16x2(r.x, sc.x); r.y = mul_bf16x2(r.y, sc.y); r.z = mul_bf16x2(r.z, sc.z); r.w = mul_bf16x2(r.w, sc.w);
    return r;
}
__device__ __forceinline__ void bulk_commit() { asm volatile("cp.async.bulk.commit_group;" ::: "memory"); }
template <int N> __device__ __forceinline__ void bulk_wait_read() { asm volatile("cp.async.bulk.wait_group.read %0;" ::"n"(N) : "memory"); }
__device__ __forceinline__ void fence_async_smem() { asm volatile("fence.proxy.async.shared::cta;" ::: "memory"); }

__device__ __forceinline__ bool mbar_try(uint32_t bar, uint32_t parity) {
    uint32_t ok;
    asm volatile("{\n.reg .pred p;\nmbarrier.try_wait.parity.shared::cta.b64 p, [%1], %2;\nselp.u32 %0, 1, 0, p;\n}\n" : "=r"(ok) : "r"(bar), "r"(parity) : "memory");
    return ok != 0;
}
__device__ __forceinline__ uint4 lds128p(uint32_t a, uint32_t on) {
    uint4 v;
    asm volatile("{\n.reg .pred p;\nsetp.ne.u32 p, %5, 0;\n@p ld.shared.v4.b32 {%0, %1, %2, %3}, [%4];\n}\n" : "=r"(v.x), "=r"(v.y), "=r"(v.z), "=r"(v.w) : "r"(a), "r"(on) : "memory");
    return v;
}
__device__ __forceinline__ void sts128p(uint32_t a, uint4 v, uint32_t on) {
    asm volatile("{\n.reg .pred p;\nsetp.ne.u32 p, %5, 0;\n@p st.shared.v4.b32 [%0], {%1, %2, %3, %4};\n}\n" ::"r"(a), "r"(v.x), "r"(v.y), "r"(v.z), "r"(v.w), "r"(on) : "memory");
}
__device__ __forceinline__ uint32_t pack4(const uint4& q) {
    uint32_t ab, cd, p;
    asm("mad.lo.u32 %0, %1, 16, %2;" : "=r"(ab) : "r"(q.y), "r"(q.x));
    asm("mad.lo.u32 %0, %1, 16, %2;" : "=r"(cd) : "r"(q.w), "r"(q.z));
    asm("mad.lo.u32 %0, %1, 256, %2;" : "=r"(p) : "r"(cd), "r"(ab));
    return p;
}
__device__ __forceinline__ uint32_t pack8(uint32_t lo, uint32_t hi) { uint32_t p; asm("mad.lo.u32 %0, %1, 65536, %2;" : "=r"(p) : "r"(hi), "r"(lo)); return p; }
__device__ __forceinline__ void lookup4s(uint32_t s7, uint32_t sel, const Lut& t, uint32_t& w01, uint32_t& w23) {
    const uint32_t lo = prmt(prmt(t.lo[0], t.lo[1], s7), prmt(t.lo[2], t.lo[3], s7), sel);
    const uint32_t hi = prmt(prmt(t.hi[0], t.hi[1], s7), prmt(t.hi[2], t.hi[3], s7), sel);
    w01 = prmt(lo, hi, 0x5140);
    w23 = prmt(lo, hi, 0x7362);
}
__device__ __forceinline__ uint4 dequant8p(uint32_t p, const uint4& sc, const Lut& t) {
    const uint32_t m8 = p & 0x88888888u, s7 = p & 0x77777777u;
    uint4 r;
    lookup4s(s7, (m8 >> 1) + 0x3210u, t, r.x, r.y);
    lookup4s(s7 >> 16, (m8 >> 17) + 0x3210u, t, r.z, r.w);
    r.x = mul_bf16x2(r.x, sc.x); r.y = mul_bf16x2(r.y, sc.y); r.z = mul_bf16x2(r.z, sc.z); r.w = mul_bf16x2(r.w, sc.w);
    return r;
}

__device__ __forceinline__ void mbar_wait2(uint32_t b0, uint32_t q0, uint32_t b1, uint32_t q1) {
    asm volatile(
        "{\n.reg .pred p0, p1;\n.reg .b32 n;\n"
        "mbarrier.try_wait.parity.shared::cta.b64 p0, [%0], %1;\n"
        "mbarrier.try_wait.parity.shared::cta.b64 p1, [%2], %3;\n"
        "and.pred p0, p0, p1;\n@p0 bra LAB_DONE;\n"
        "mov.b32 n, 0;\n"
        "LAB_WAIT:\n"
        "mbarrier.try_wait.parity.shared::cta.b64 p0, [%0], %1;\n"
        "mbarrier.try_wait.parity.shared::cta.b64 p1, [%2], %3;\n"
        "and.pred p0, p0, p1;\n@p0 bra LAB_DONE;\n"
        "add.u32 n, n, 1;\n"
        "setp.lt.u32 p0, n, 0x40000;\n"
        "@p0 bra LAB_WAIT;\n"
        "trap;\n"
        "LAB_DONE:\n}\n" ::"r"(b0), "r"(q0), "r"(b1), "r"(q1) : "memory");
}
__device__ __forceinline__ void mbar_wait3(uint32_t b0, uint32_t q0, uint32_t b1, uint32_t q1, uint32_t b2, uint32_t q2) {
    asm volatile(
        "{\n.reg .pred p0, p1, p2;\n.reg .b32 n;\n"
        "mbarrier.try_wait.parity.shared::cta.b64 p0, [%0], %1;\n"
        "mbarrier.try_wait.parity.shared::cta.b64 p1, [%2], %3;\n"
        "mbarrier.try_wait.parity.shared::cta.b64 p2, [%4], %5;\n"
        "and.pred p0, p0, p1;\nand.pred p0, p0, p2;\n@p0 bra LAB_DONE;\n"
        "mov.b32 n, 0;\n"
        "LAB_WAIT:\n"
        "mbarrier.try_wait.parity.shared::cta.b64 p0, [%0], %1;\n"
        "mbarrier.try_wait.parity.shared::cta.b64 p1, [%2], %3;\n"
        "mbarrier.try_wait.parity.shared::cta.b64 p2, [%4], %5;\n"
        "and.pred p0, p0, p1;\nand.pred p0, p0, p2;\n@p0 bra LAB_DONE;\n"
        "add.u32 n, n, 1;\n"
        "setp.lt.u32 p0, n, 0x40000;\n"
        "@p0 bra LAB_WAIT;\n"
        "trap;\n"
        "LAB_DONE:\n}\n" ::"r"(b0), "r"(q0), "r"(b1), "r"(q1), "r"(b2), "r"(q2) : "memory");
}
__device__ __forceinline__ void mbar_wait4(uint32_t b0, uint32_t q0, uint32_t b1, uint32_t q1, uint32_t b2, uint32_t q2, uint32_t b3, uint32_t q3) {
    asm volatile(
        "{\n.reg .pred p0, p1, p2, p3;\n.reg .b32 n;\n"
        "mbarrier.try_wait.parity.shared::cta.b64 p0, [%0], %1;\n"
        "mbarrier.try_wait.parity.shared::cta.b64 p1, [%2], %3;\n"
        "mbarrier.try_wait.parity.shared::cta.b64 p2, [%4], %5;\n"
        "mbarrier.try_wait.parity.shared::cta.b64 p3, [%6], %7;\n"
        "and.pred p0, p0, p1;\nand.pred p0, p0, p2;\nand.pred p0, p0, p3;\n@p0 bra LAB_DONE;\n"
        "mov.b32 n, 0;\n"
        "LAB_WAIT:\n"
        "mbarrier.try_wait.parity.shared::cta.b64 p0, [%0], %1;\n"
        "mbarrier.try_wait.parity.shared::cta.b64 p1, [%2], %3;\n"
        "mbarrier.try_wait.parity.shared::cta.b64 p2, [%4], %5;\n"
        "mbarrier.try_wait.parity.shared::cta.b64 p3, [%6], %7;\n"
        "and.pred p0, p0, p1;\nand.pred p0, p0, p2;\nand.pred p0, p0, p3;\n@p0 bra LAB_DONE;\n"
        "add.u32 n, n, 1;\n"
        "setp.lt.u32 p0, n, 0x40000;\n"
        "@p0 bra LAB_WAIT;\n"
        "trap;\n"
        "LAB_DONE:\n}\n" ::"r"(b0), "r"(q0), "r"(b1), "r"(q1), "r"(b2), "r"(q2), "r"(b3), "r"(q3) : "memory");
}

__device__ __forceinline__ uint32_t madi(uint32_t hi, uint32_t m, uint32_t lo) { uint32_t r; asm("mad.lo.u32 %0, %1, %2, %3;" : "=r"(r) : "r"(hi), "r"(m), "r"(lo)); return r; }
__device__ __forceinline__ void pack16(const uint4& a, const uint4& b, const uint4& c, const uint4& d, uint32_t& p1, uint32_t& p2) {
    p1 = madi(madi(madi(d.y, 65536, b.y), 256, madi(c.y, 65536, a.y)), 16, madi(madi(d.x, 256, c.x), 65536, madi(b.x, 256, a.x)));
    p2 = madi(madi(madi(d.w, 256, c.w), 65536, madi(b.w, 256, a.w)), 16, madi(madi(c.z, 256, b.z), 256, madi(d.z, 1 << 24, a.z)));
}
template <int HI>
__device__ __forceinline__ uint4 dequant16(uint32_t p1, uint32_t p2, const uint4& sc, const Lut& t) {
    uint4 r;
    lookup4s((p1 & 0x77777777u) >> (16 * HI), ((p1 & 0x88888888u) >> (16 * HI + 1)) + 0x3210u, t, r.x, r.z);
    lookup4s((p2 & 0x77777777u) >> (16 * HI), ((p2 & 0x88888888u) >> (16 * HI + 1)) + 0x3210u, t, r.y, r.w);
    r.x = mul_bf16x2(r.x, sc.x); r.y = mul_bf16x2(r.y, sc.y); r.z = mul_bf16x2(r.z, sc.z); r.w = mul_bf16x2(r.w, sc.w);
    return r;
}

__device__ __forceinline__ void bulk_load_mc(uint32_t dst, const void* src, uint32_t bytes, uint32_t bar) {
    asm volatile("cp.async.bulk.shared::cluster.global.mbarrier::complete_tx::bytes.multicast::cluster [%0], [%1], %2, [%3], %4;"
                 ::"r"(dst), "l"(src), "r"(bytes), "r"(bar), "h"((uint16_t)3) : "memory");
}
__device__ __forceinline__ unsigned store_probed(void* p, uint4 v) {
    unsigned r;
    asm volatile("st.global.v4.b32 [%1], {%2, %3, %4, %5};\natom.relaxed.gpu.global.exch.b32 %0, [%1], %2;"
                 : "=r"(r) : "l"(p), "r"(v.x), "r"(v.y), "r"(v.z), "r"(v.w) : "memory");
    return r;
}
__device__ __forceinline__ unsigned after(unsigned n, unsigned p, unsigned z) {
    unsigned r; asm volatile("lop3.b32 %0, %1, %2, %3, 0xea;" : "=r"(r) : "r"(p), "r"(z), "r"(n)); return r;
}
__device__ __forceinline__ void red_add(unsigned* f, unsigned n) { asm volatile("red.relaxed.gpu.global.add.u32 [%0], %1;" ::"l"(f), "r"(n) : "memory"); }
__device__ __forceinline__ unsigned ld_relaxed(const unsigned* p) {
    unsigned v; asm volatile("ld.relaxed.gpu.global.u32 %0, [%1];" : "=r"(v) : "l"(p) : "memory"); return v;
}

__device__ __forceinline__ void tma_load_3d(uint32_t dst, const CUtensorMap* tm, int c0, int c1, int c2, uint32_t bar) {
    asm volatile("cp.async.bulk.tensor.3d.shared::cluster.global.mbarrier::complete_tx::bytes [%0], [%1, {%2, %3, %4}], [%5];"
                 ::"r"(dst), "l"(tm), "r"(c0), "r"(c1), "r"(c2), "r"(bar) : "memory");
}
__device__ __forceinline__ void tma_store_2d(const CUtensorMap* tm, uint32_t src, int c0, int c1) {
    asm volatile("cp.async.bulk.tensor.2d.global.shared::cta.bulk_group [%0, {%2, %3}], [%1];"
                 ::"l"(tm), "r"(src), "r"(c0), "r"(c1) : "memory");
}
__device__ __forceinline__ void mbar_arrive_n(uint32_t bar, uint32_t n) { asm volatile("mbarrier.arrive.shared::cta.b64 _, [%0], %1;" ::"r"(bar), "r"(n) : "memory"); }

__device__ __forceinline__ uint2 lds64(uint32_t a) {
    uint2 v; asm volatile("ld.shared.v2.b32 {%0, %1}, [%2];" : "=r"(v.x), "=r"(v.y) : "r"(a) : "memory"); return v;
}
__device__ __forceinline__ uint32_t lds32(uint32_t a) {
    uint32_t v; asm volatile("ld.shared.b32 %0, [%1];" : "=r"(v) : "r"(a) : "memory"); return v;
}
__device__ __forceinline__ void st_async128(uint32_t raddr, uint4 v, uint32_t rbar) {
    asm volatile("st.async.shared::cluster.mbarrier::complete_tx::bytes.v4.b32 [%0], {%1, %2, %3, %4}, [%5];"
                 ::"r"(raddr), "r"(v.x), "r"(v.y), "r"(v.z), "r"(v.w), "r"(rbar) : "memory");
}
__device__ __forceinline__ void stg128(void* p, uint32_t a, uint32_t b, uint32_t c, uint32_t d) {
    asm volatile("st.global.v4.b32 [%0], {%1, %2, %3, %4};" ::"l"(p), "r"(a), "r"(b), "r"(c), "r"(d) : "memory");
}

__device__ __forceinline__ void tma_prefetch_3d(const CUtensorMap* tm, int c0, int c1, int c2) {
    asm volatile("cp.async.bulk.prefetch.tensor.3d.L2.global [%0, {%1, %2, %3}];" ::"l"(tm), "r"(c0), "r"(c1), "r"(c2) : "memory");
}
__device__ __forceinline__ void sts32(uint32_t a, uint32_t v) { asm volatile("st.shared.b32 [%0], %1;" ::"r"(a), "r"(v) : "memory"); }
__device__ __forceinline__ void stg32(void* p, uint32_t v) { asm volatile("st.global.b32 [%0], %1;" ::"l"(p), "r"(v) : "memory"); }
__device__ __forceinline__ void probe_l2(uint32_t dst, const void* src, uint32_t on) {
    asm volatile("{\n.reg .pred p;\nsetp.ne.u32 p, %2, 0;\n@p cp.async.cg.shared.global [%0], [%1], 16;\n}\ncp.async.commit_group;" ::"r"(dst), "l"(src), "r"(on) : "memory");
}
template <int N> __device__ __forceinline__ void probe_wait() { asm volatile("cp.async.wait_group %0;" ::"n"(N) : "memory"); }

__device__ __forceinline__ void probe_arrive(uint32_t bar) { asm volatile("cp.async.mbarrier.arrive.noinc.shared::cta.b64 [%0];" ::"r"(bar) : "memory"); }
__device__ __forceinline__ void poll_ge(const unsigned* f, unsigned v, unsigned ready) {
    asm volatile(
        "{\n.reg .pred p;\n.reg .b32 v, n;\n"
        "setp.lt.u32 p, %1, %2;\n"
        "vote.sync.any.pred p, p, 0xffffffff;\n"
        "@!p bra.uni LAB_DONE;\n"
        "mov.b32 n, 0;\n"
        "LAB_POLL:\n"
        "ld.relaxed.gpu.global.u32 v, [%0];\n"
        "setp.lt.u32 p, v, %2;\n"
        "vote.sync.any.pred p, p, 0xffffffff;\n"
        "@!p bra.uni LAB_DONE;\n"
        "add.u32 n, n, 1;\n"
        "setp.lt.u32 p, n, 0x400000;\n"
        "@p bra.uni LAB_POLL;\n"
        "LAB_DONE:\n}\n" ::"l"(f), "r"(v), "r"(ready) : "memory");
}

__device__ __forceinline__ void delay(unsigned clks) {
    asm volatile(
        "{\n.reg .pred p;\n.reg .b32 t0, t;\n"
        "mov.u32 t0, %%clock;\n"
        "LAB_DELAY:\n"
        "mov.u32 t, %%clock;\n"
        "sub.u32 t, t, t0;\n"
        "setp.lt.u32 p, t, %0;\n"
        "vote.sync.any.pred p, p, 0xffffffff;\n"
        "@p bra.uni LAB_DELAY;\n}\n" ::"r"(clks) : "memory");
}

template <int I> struct IC { static constexpr int value = I; };
template <int I, int N, class F> __device__ __forceinline__ void static_for(F&& f) {
    if constexpr (I < N) { f(IC<I>{}); static_for<I + 1, N>(f); }
}

__device__ __forceinline__ uint4 ldmatrix_x4(uint32_t a) {
    uint4 v;
    asm volatile("ldmatrix.sync.aligned.m8n8.x4.shared.b16 {%0, %1, %2, %3}, [%4];" : "=r"(v.x), "=r"(v.y), "=r"(v.z), "=r"(v.w) : "r"(a) : "memory");
    return v;
}

__device__ __forceinline__ void poll_fast(const void* f, uint32_t w, uint32_t buf, unsigned ready, unsigned gap) {
    asm volatile(
        "{\n.reg .pred p, e;\n.reg .b32 v, n, s, a, t0, t;\n"
        "elect.sync _|e, 0xffffffff;\n"
        "mov.b32 n, 0;\nmov.b32 s, 0;\n"
        "LAB_POLL:\n"
        "add.u32 a, %2, s;\n"
        "@e cp.async.cg.shared.global [a], [%0], 16;\n"
        "cp.async.commit_group;\n"
        "add.u32 s, s, 16;\nsetp.eq.u32 p, s, 80;\nselp.b32 s, 0, s, p;\n"
        "add.u32 n, n, 1;\n"
        "mov.u32 t0, %%clock;\n"
        "LAB_GAP:\n"
        "mov.u32 t, %%clock;\nsub.u32 t, t, t0;\nsetp.lt.u32 p, t, %4;\n"
        "vote.sync.any.pred p, p, 0xffffffff;\n"
        "@p bra.uni LAB_GAP;\n"
        "setp.lt.u32 p, n, 5;\n"
        "@p bra.uni LAB_POLL;\n"
        "cp.async.wait_group 4;\n"
        "bar.warp.sync 0xffffffff;\n"
        "add.u32 a, %2, s;\nadd.u32 a, a, %1;\n"
        "ld.shared.u32 v, [a];\n"
        "setp.lt.u32 p, v, %3;\n"
        "vote.sync.any.pred p, p, 0xffffffff;\n"
        "@!p bra.uni LAB_DONE;\n"
        "setp.lt.u32 p, n, 0x400000;\n"
        "@p bra.uni LAB_POLL;\n"
        "LAB_DONE:\n}\n" ::"l"(f), "r"(w * 4), "r"(buf), "r"(ready), "r"(gap) : "memory");
}

template <int SCALE_D>
__device__ __forceinline__ void wgmma_ss(float (&d)[112], uint32_t descA, uint32_t descB) {
    asm volatile(
        "{\n.reg .pred p;\n.reg .b64 da, db;\nsetp.ne.b32 p, %114, 0;\n"
        "mov.b64 da, {%112, 0x40000040};\nmov.b64 db, {%113, 0x10};\n"
        "wgmma.mma_async.sync.aligned.m64n224k16.f32.bf16.bf16 "
        "{%0, %1, %2, %3, %4, %5, %6, %7, %8, %9, %10, %11, %12, %13, %14, %15, "
        "%16, %17, %18, %19, %20, %21, %22, %23, %24, %25, %26, %27, %28, %29, %30, %31, "
        "%32, %33, %34, %35, %36, %37, %38, %39, %40, %41, %42, %43, %44, %45, %46, %47, "
        "%48, %49, %50, %51, %52, %53, %54, %55, %56, %57, %58, %59, %60, %61, %62, %63, "
        "%64, %65, %66, %67, %68, %69, %70, %71, %72, %73, %74, %75, %76, %77, %78, %79, "
        "%80, %81, %82, %83, %84, %85, %86, %87, %88, %89, %90, %91, %92, %93, %94, %95, "
        "%96, %97, %98, %99, %100, %101, %102, %103, %104, %105, %106, %107, %108, %109, %110, %111}, "
        "da, db, p, 1, 1, 0, 1;\n}\n"
        : "+f"(d[0]), "+f"(d[1]), "+f"(d[2]), "+f"(d[3]), "+f"(d[4]), "+f"(d[5]), "+f"(d[6]), "+f"(d[7]),
          "+f"(d[8]), "+f"(d[9]), "+f"(d[10]), "+f"(d[11]), "+f"(d[12]), "+f"(d[13]), "+f"(d[14]), "+f"(d[15]),
          "+f"(d[16]), "+f"(d[17]), "+f"(d[18]), "+f"(d[19]), "+f"(d[20]), "+f"(d[21]), "+f"(d[22]), "+f"(d[23]),
          "+f"(d[24]), "+f"(d[25]), "+f"(d[26]), "+f"(d[27]), "+f"(d[28]), "+f"(d[29]), "+f"(d[30]), "+f"(d[31]),
          "+f"(d[32]), "+f"(d[33]), "+f"(d[34]), "+f"(d[35]), "+f"(d[36]), "+f"(d[37]), "+f"(d[38]), "+f"(d[39]),
          "+f"(d[40]), "+f"(d[41]), "+f"(d[42]), "+f"(d[43]), "+f"(d[44]), "+f"(d[45]), "+f"(d[46]), "+f"(d[47]),
          "+f"(d[48]), "+f"(d[49]), "+f"(d[50]), "+f"(d[51]), "+f"(d[52]), "+f"(d[53]), "+f"(d[54]), "+f"(d[55]),
          "+f"(d[56]), "+f"(d[57]), "+f"(d[58]), "+f"(d[59]), "+f"(d[60]), "+f"(d[61]), "+f"(d[62]), "+f"(d[63]),
          "+f"(d[64]), "+f"(d[65]), "+f"(d[66]), "+f"(d[67]), "+f"(d[68]), "+f"(d[69]), "+f"(d[70]), "+f"(d[71]),
          "+f"(d[72]), "+f"(d[73]), "+f"(d[74]), "+f"(d[75]), "+f"(d[76]), "+f"(d[77]), "+f"(d[78]), "+f"(d[79]),
          "+f"(d[80]), "+f"(d[81]), "+f"(d[82]), "+f"(d[83]), "+f"(d[84]), "+f"(d[85]), "+f"(d[86]), "+f"(d[87]),
          "+f"(d[88]), "+f"(d[89]), "+f"(d[90]), "+f"(d[91]), "+f"(d[92]), "+f"(d[93]), "+f"(d[94]), "+f"(d[95]),
          "+f"(d[96]), "+f"(d[97]), "+f"(d[98]), "+f"(d[99]), "+f"(d[100]), "+f"(d[101]), "+f"(d[102]), "+f"(d[103]),
          "+f"(d[104]), "+f"(d[105]), "+f"(d[106]), "+f"(d[107]), "+f"(d[108]), "+f"(d[109]), "+f"(d[110]), "+f"(d[111])
        : "r"(descA), "r"(descB), "n"(SCALE_D));
}

template <int SCALE_D>
__device__ __forceinline__ void wgmma_ss(float (&d)[80], uint32_t descA, uint32_t descB) {
    asm volatile(
        "{\n.reg .pred p;\n.reg .b64 da, db;\nsetp.ne.b32 p, %82, 0;\n"
        "mov.b64 da, {%80, 0x40000040};\nmov.b64 db, {%81, 0x10};\n"
        "wgmma.mma_async.sync.aligned.m64n160k16.f32.bf16.bf16 "
        "{%0, %1, %2, %3, %4, %5, %6, %7, %8, %9, %10, %11, %12, %13, %14, %15, "
        "%16, %17, %18, %19, %20, %21, %22, %23, %24, %25, %26, %27, %28, %29, %30, %31, "
        "%32, %33, %34, %35, %36, %37, %38, %39, %40, %41, %42, %43, %44, %45, %46, %47, "
        "%48, %49, %50, %51, %52, %53, %54, %55, %56, %57, %58, %59, %60, %61, %62, %63, "
        "%64, %65, %66, %67, %68, %69, %70, %71, %72, %73, %74, %75, %76, %77, %78, %79}, "
        "da, db, p, 1, 1, 0, 1;\n}\n"
        : "+f"(d[0]), "+f"(d[1]), "+f"(d[2]), "+f"(d[3]), "+f"(d[4]), "+f"(d[5]), "+f"(d[6]), "+f"(d[7]),
          "+f"(d[8]), "+f"(d[9]), "+f"(d[10]), "+f"(d[11]), "+f"(d[12]), "+f"(d[13]), "+f"(d[14]), "+f"(d[15]),
          "+f"(d[16]), "+f"(d[17]), "+f"(d[18]), "+f"(d[19]), "+f"(d[20]), "+f"(d[21]), "+f"(d[22]), "+f"(d[23]),
          "+f"(d[24]), "+f"(d[25]), "+f"(d[26]), "+f"(d[27]), "+f"(d[28]), "+f"(d[29]), "+f"(d[30]), "+f"(d[31]),
          "+f"(d[32]), "+f"(d[33]), "+f"(d[34]), "+f"(d[35]), "+f"(d[36]), "+f"(d[37]), "+f"(d[38]), "+f"(d[39]),
          "+f"(d[40]), "+f"(d[41]), "+f"(d[42]), "+f"(d[43]), "+f"(d[44]), "+f"(d[45]), "+f"(d[46]), "+f"(d[47]),
          "+f"(d[48]), "+f"(d[49]), "+f"(d[50]), "+f"(d[51]), "+f"(d[52]), "+f"(d[53]), "+f"(d[54]), "+f"(d[55]),
          "+f"(d[56]), "+f"(d[57]), "+f"(d[58]), "+f"(d[59]), "+f"(d[60]), "+f"(d[61]), "+f"(d[62]), "+f"(d[63]),
          "+f"(d[64]), "+f"(d[65]), "+f"(d[66]), "+f"(d[67]), "+f"(d[68]), "+f"(d[69]), "+f"(d[70]), "+f"(d[71]),
          "+f"(d[72]), "+f"(d[73]), "+f"(d[74]), "+f"(d[75]), "+f"(d[76]), "+f"(d[77]), "+f"(d[78]), "+f"(d[79])
        : "r"(descA), "r"(descB), "n"(SCALE_D));
}

template <int SCALE_D>
__device__ __forceinline__ void wgmma_ss(float (&d)[64], uint32_t descA, uint32_t descB) {
    asm volatile(
        "{\n.reg .pred p;\n.reg .b64 da, db;\nsetp.ne.b32 p, %66, 0;\n"
        "mov.b64 da, {%64, 0x40000040};\nmov.b64 db, {%65, 0x10};\n"
        "wgmma.mma_async.sync.aligned.m64n128k16.f32.bf16.bf16 "
        "{%0, %1, %2, %3, %4, %5, %6, %7, %8, %9, %10, %11, %12, %13, %14, %15, "
        "%16, %17, %18, %19, %20, %21, %22, %23, %24, %25, %26, %27, %28, %29, %30, %31, "
        "%32, %33, %34, %35, %36, %37, %38, %39, %40, %41, %42, %43, %44, %45, %46, %47, "
        "%48, %49, %50, %51, %52, %53, %54, %55, %56, %57, %58, %59, %60, %61, %62, %63}, "
        "da, db, p, 1, 1, 0, 1;\n}\n"
        : "+f"(d[0]), "+f"(d[1]), "+f"(d[2]), "+f"(d[3]), "+f"(d[4]), "+f"(d[5]), "+f"(d[6]), "+f"(d[7]),
          "+f"(d[8]), "+f"(d[9]), "+f"(d[10]), "+f"(d[11]), "+f"(d[12]), "+f"(d[13]), "+f"(d[14]), "+f"(d[15]),
          "+f"(d[16]), "+f"(d[17]), "+f"(d[18]), "+f"(d[19]), "+f"(d[20]), "+f"(d[21]), "+f"(d[22]), "+f"(d[23]),
          "+f"(d[24]), "+f"(d[25]), "+f"(d[26]), "+f"(d[27]), "+f"(d[28]), "+f"(d[29]), "+f"(d[30]), "+f"(d[31]),
          "+f"(d[32]), "+f"(d[33]), "+f"(d[34]), "+f"(d[35]), "+f"(d[36]), "+f"(d[37]), "+f"(d[38]), "+f"(d[39]),
          "+f"(d[40]), "+f"(d[41]), "+f"(d[42]), "+f"(d[43]), "+f"(d[44]), "+f"(d[45]), "+f"(d[46]), "+f"(d[47]),
          "+f"(d[48]), "+f"(d[49]), "+f"(d[50]), "+f"(d[51]), "+f"(d[52]), "+f"(d[53]), "+f"(d[54]), "+f"(d[55]),
          "+f"(d[56]), "+f"(d[57]), "+f"(d[58]), "+f"(d[59]), "+f"(d[60]), "+f"(d[61]), "+f"(d[62]), "+f"(d[63])
        : "r"(descA), "r"(descB), "n"(SCALE_D));
}

template <int SCALE_D>
__device__ __forceinline__ void wgmma_ss(float (&d)[48], uint32_t descA, uint32_t descB) {
    asm volatile(
        "{\n.reg .pred p;\n.reg .b64 da, db;\nsetp.ne.b32 p, %50, 0;\n"
        "mov.b64 da, {%48, 0x40000040};\nmov.b64 db, {%49, 0x10};\n"
        "wgmma.mma_async.sync.aligned.m64n96k16.f32.bf16.bf16 "
        "{%0, %1, %2, %3, %4, %5, %6, %7, %8, %9, %10, %11, %12, %13, %14, %15, "
        "%16, %17, %18, %19, %20, %21, %22, %23, %24, %25, %26, %27, %28, %29, %30, %31, "
        "%32, %33, %34, %35, %36, %37, %38, %39, %40, %41, %42, %43, %44, %45, %46, %47}, "
        "da, db, p, 1, 1, 0, 1;\n}\n"
        : "+f"(d[0]), "+f"(d[1]), "+f"(d[2]), "+f"(d[3]), "+f"(d[4]), "+f"(d[5]), "+f"(d[6]), "+f"(d[7]),
          "+f"(d[8]), "+f"(d[9]), "+f"(d[10]), "+f"(d[11]), "+f"(d[12]), "+f"(d[13]), "+f"(d[14]), "+f"(d[15]),
          "+f"(d[16]), "+f"(d[17]), "+f"(d[18]), "+f"(d[19]), "+f"(d[20]), "+f"(d[21]), "+f"(d[22]), "+f"(d[23]),
          "+f"(d[24]), "+f"(d[25]), "+f"(d[26]), "+f"(d[27]), "+f"(d[28]), "+f"(d[29]), "+f"(d[30]), "+f"(d[31]),
          "+f"(d[32]), "+f"(d[33]), "+f"(d[34]), "+f"(d[35]), "+f"(d[36]), "+f"(d[37]), "+f"(d[38]), "+f"(d[39]),
          "+f"(d[40]), "+f"(d[41]), "+f"(d[42]), "+f"(d[43]), "+f"(d[44]), "+f"(d[45]), "+f"(d[46]), "+f"(d[47])
        : "r"(descA), "r"(descB), "n"(SCALE_D));
}

template <int SCALE_D>
__device__ __forceinline__ void wgmma_ss(float (&d)[32], uint32_t descA, uint32_t descB) {
    asm volatile(
        "{\n.reg .pred p;\n.reg .b64 da, db;\nsetp.ne.b32 p, %34, 0;\n"
        "mov.b64 da, {%32, 0x40000040};\nmov.b64 db, {%33, 0x10};\n"
        "wgmma.mma_async.sync.aligned.m64n64k16.f32.bf16.bf16 "
        "{%0, %1, %2, %3, %4, %5, %6, %7, %8, %9, %10, %11, %12, %13, %14, %15, "
        "%16, %17, %18, %19, %20, %21, %22, %23, %24, %25, %26, %27, %28, %29, %30, %31}, "
        "da, db, p, 1, 1, 0, 1;\n}\n"
        : "+f"(d[0]), "+f"(d[1]), "+f"(d[2]), "+f"(d[3]), "+f"(d[4]), "+f"(d[5]), "+f"(d[6]), "+f"(d[7]),
          "+f"(d[8]), "+f"(d[9]), "+f"(d[10]), "+f"(d[11]), "+f"(d[12]), "+f"(d[13]), "+f"(d[14]), "+f"(d[15]),
          "+f"(d[16]), "+f"(d[17]), "+f"(d[18]), "+f"(d[19]), "+f"(d[20]), "+f"(d[21]), "+f"(d[22]), "+f"(d[23]),
          "+f"(d[24]), "+f"(d[25]), "+f"(d[26]), "+f"(d[27]), "+f"(d[28]), "+f"(d[29]), "+f"(d[30]), "+f"(d[31])
        : "r"(descA), "r"(descB), "n"(SCALE_D));
}

template <int SCALE_D>
__device__ __forceinline__ void wgmma_ss(float (&d)[16], uint32_t descA, uint32_t descB) {
    asm volatile(
        "{\n.reg .pred p;\n.reg .b64 da, db;\nsetp.ne.b32 p, %18, 0;\n"
        "mov.b64 da, {%16, 0x40000040};\nmov.b64 db, {%17, 0x10};\n"
        "wgmma.mma_async.sync.aligned.m64n32k16.f32.bf16.bf16 "
        "{%0, %1, %2, %3, %4, %5, %6, %7, %8, %9, %10, %11, %12, %13, %14, %15}, "
        "da, db, p, 1, 1, 0, 1;\n}\n"
        : "+f"(d[0]), "+f"(d[1]), "+f"(d[2]), "+f"(d[3]), "+f"(d[4]), "+f"(d[5]), "+f"(d[6]), "+f"(d[7]),
          "+f"(d[8]), "+f"(d[9]), "+f"(d[10]), "+f"(d[11]), "+f"(d[12]), "+f"(d[13]), "+f"(d[14]), "+f"(d[15])
        : "r"(descA), "r"(descB), "n"(SCALE_D));
}

__device__ __forceinline__ void wgmma_rs(float (&d)[80], const uint4& a, uint32_t descB) {
    asm volatile(
        "{\n.reg .pred p;\n.reg .b64 db;\nsetp.eq.b32 p, 0, 0;\n"
        "mov.b64 db, {%84, 0x10};\n"
        "wgmma.mma_async.sync.aligned.m64n160k16.f32.bf16.bf16 "
        "{%0, %1, %2, %3, %4, %5, %6, %7, %8, %9, %10, %11, %12, %13, %14, %15, "
        "%16, %17, %18, %19, %20, %21, %22, %23, %24, %25, %26, %27, %28, %29, %30, %31, "
        "%32, %33, %34, %35, %36, %37, %38, %39, %40, %41, %42, %43, %44, %45, %46, %47, "
        "%48, %49, %50, %51, %52, %53, %54, %55, %56, %57, %58, %59, %60, %61, %62, %63, "
        "%64, %65, %66, %67, %68, %69, %70, %71, %72, %73, %74, %75, %76, %77, %78, %79}, "
        "{%80, %81, %82, %83}, db, p, 1, 1, 1;\n}\n"
        : "+f"(d[0]), "+f"(d[1]), "+f"(d[2]), "+f"(d[3]), "+f"(d[4]), "+f"(d[5]), "+f"(d[6]), "+f"(d[7]),
          "+f"(d[8]), "+f"(d[9]), "+f"(d[10]), "+f"(d[11]), "+f"(d[12]), "+f"(d[13]), "+f"(d[14]), "+f"(d[15]),
          "+f"(d[16]), "+f"(d[17]), "+f"(d[18]), "+f"(d[19]), "+f"(d[20]), "+f"(d[21]), "+f"(d[22]), "+f"(d[23]),
          "+f"(d[24]), "+f"(d[25]), "+f"(d[26]), "+f"(d[27]), "+f"(d[28]), "+f"(d[29]), "+f"(d[30]), "+f"(d[31]),
          "+f"(d[32]), "+f"(d[33]), "+f"(d[34]), "+f"(d[35]), "+f"(d[36]), "+f"(d[37]), "+f"(d[38]), "+f"(d[39]),
          "+f"(d[40]), "+f"(d[41]), "+f"(d[42]), "+f"(d[43]), "+f"(d[44]), "+f"(d[45]), "+f"(d[46]), "+f"(d[47]),
          "+f"(d[48]), "+f"(d[49]), "+f"(d[50]), "+f"(d[51]), "+f"(d[52]), "+f"(d[53]), "+f"(d[54]), "+f"(d[55]),
          "+f"(d[56]), "+f"(d[57]), "+f"(d[58]), "+f"(d[59]), "+f"(d[60]), "+f"(d[61]), "+f"(d[62]), "+f"(d[63]),
          "+f"(d[64]), "+f"(d[65]), "+f"(d[66]), "+f"(d[67]), "+f"(d[68]), "+f"(d[69]), "+f"(d[70]), "+f"(d[71]),
          "+f"(d[72]), "+f"(d[73]), "+f"(d[74]), "+f"(d[75]), "+f"(d[76]), "+f"(d[77]), "+f"(d[78]), "+f"(d[79])
        : "r"(a.x), "r"(a.y), "r"(a.z), "r"(a.w), "r"(descB));
}

__device__ __forceinline__ void wgmma_rs(float (&d)[64], const uint4& a, uint32_t descB) {
    asm volatile(
        "{\n.reg .pred p;\n.reg .b64 db;\nsetp.eq.b32 p, 0, 0;\n"
        "mov.b64 db, {%68, 0x10};\n"
        "wgmma.mma_async.sync.aligned.m64n128k16.f32.bf16.bf16 "
        "{%0, %1, %2, %3, %4, %5, %6, %7, %8, %9, %10, %11, %12, %13, %14, %15, "
        "%16, %17, %18, %19, %20, %21, %22, %23, %24, %25, %26, %27, %28, %29, %30, %31, "
        "%32, %33, %34, %35, %36, %37, %38, %39, %40, %41, %42, %43, %44, %45, %46, %47, "
        "%48, %49, %50, %51, %52, %53, %54, %55, %56, %57, %58, %59, %60, %61, %62, %63}, "
        "{%64, %65, %66, %67}, db, p, 1, 1, 1;\n}\n"
        : "+f"(d[0]), "+f"(d[1]), "+f"(d[2]), "+f"(d[3]), "+f"(d[4]), "+f"(d[5]), "+f"(d[6]), "+f"(d[7]),
          "+f"(d[8]), "+f"(d[9]), "+f"(d[10]), "+f"(d[11]), "+f"(d[12]), "+f"(d[13]), "+f"(d[14]), "+f"(d[15]),
          "+f"(d[16]), "+f"(d[17]), "+f"(d[18]), "+f"(d[19]), "+f"(d[20]), "+f"(d[21]), "+f"(d[22]), "+f"(d[23]),
          "+f"(d[24]), "+f"(d[25]), "+f"(d[26]), "+f"(d[27]), "+f"(d[28]), "+f"(d[29]), "+f"(d[30]), "+f"(d[31]),
          "+f"(d[32]), "+f"(d[33]), "+f"(d[34]), "+f"(d[35]), "+f"(d[36]), "+f"(d[37]), "+f"(d[38]), "+f"(d[39]),
          "+f"(d[40]), "+f"(d[41]), "+f"(d[42]), "+f"(d[43]), "+f"(d[44]), "+f"(d[45]), "+f"(d[46]), "+f"(d[47]),
          "+f"(d[48]), "+f"(d[49]), "+f"(d[50]), "+f"(d[51]), "+f"(d[52]), "+f"(d[53]), "+f"(d[54]), "+f"(d[55]),
          "+f"(d[56]), "+f"(d[57]), "+f"(d[58]), "+f"(d[59]), "+f"(d[60]), "+f"(d[61]), "+f"(d[62]), "+f"(d[63])
        : "r"(a.x), "r"(a.y), "r"(a.z), "r"(a.w), "r"(descB));
}

__device__ __forceinline__ void wgmma_rs(float (&d)[48], const uint4& a, uint32_t descB) {
    asm volatile(
        "{\n.reg .pred p;\n.reg .b64 db;\nsetp.eq.b32 p, 0, 0;\n"
        "mov.b64 db, {%52, 0x10};\n"
        "wgmma.mma_async.sync.aligned.m64n96k16.f32.bf16.bf16 "
        "{%0, %1, %2, %3, %4, %5, %6, %7, %8, %9, %10, %11, %12, %13, %14, %15, "
        "%16, %17, %18, %19, %20, %21, %22, %23, %24, %25, %26, %27, %28, %29, %30, %31, "
        "%32, %33, %34, %35, %36, %37, %38, %39, %40, %41, %42, %43, %44, %45, %46, %47}, "
        "{%48, %49, %50, %51}, db, p, 1, 1, 1;\n}\n"
        : "+f"(d[0]), "+f"(d[1]), "+f"(d[2]), "+f"(d[3]), "+f"(d[4]), "+f"(d[5]), "+f"(d[6]), "+f"(d[7]),
          "+f"(d[8]), "+f"(d[9]), "+f"(d[10]), "+f"(d[11]), "+f"(d[12]), "+f"(d[13]), "+f"(d[14]), "+f"(d[15]),
          "+f"(d[16]), "+f"(d[17]), "+f"(d[18]), "+f"(d[19]), "+f"(d[20]), "+f"(d[21]), "+f"(d[22]), "+f"(d[23]),
          "+f"(d[24]), "+f"(d[25]), "+f"(d[26]), "+f"(d[27]), "+f"(d[28]), "+f"(d[29]), "+f"(d[30]), "+f"(d[31]),
          "+f"(d[32]), "+f"(d[33]), "+f"(d[34]), "+f"(d[35]), "+f"(d[36]), "+f"(d[37]), "+f"(d[38]), "+f"(d[39]),
          "+f"(d[40]), "+f"(d[41]), "+f"(d[42]), "+f"(d[43]), "+f"(d[44]), "+f"(d[45]), "+f"(d[46]), "+f"(d[47])
        : "r"(a.x), "r"(a.y), "r"(a.z), "r"(a.w), "r"(descB));
}

__device__ __forceinline__ void wgmma_rs(float (&d)[32], const uint4& a, uint32_t descB) {
    asm volatile(
        "{\n.reg .pred p;\n.reg .b64 db;\nsetp.eq.b32 p, 0, 0;\n"
        "mov.b64 db, {%36, 0x10};\n"
        "wgmma.mma_async.sync.aligned.m64n64k16.f32.bf16.bf16 "
        "{%0, %1, %2, %3, %4, %5, %6, %7, %8, %9, %10, %11, %12, %13, %14, %15, "
        "%16, %17, %18, %19, %20, %21, %22, %23, %24, %25, %26, %27, %28, %29, %30, %31}, "
        "{%32, %33, %34, %35}, db, p, 1, 1, 1;\n}\n"
        : "+f"(d[0]), "+f"(d[1]), "+f"(d[2]), "+f"(d[3]), "+f"(d[4]), "+f"(d[5]), "+f"(d[6]), "+f"(d[7]),
          "+f"(d[8]), "+f"(d[9]), "+f"(d[10]), "+f"(d[11]), "+f"(d[12]), "+f"(d[13]), "+f"(d[14]), "+f"(d[15]),
          "+f"(d[16]), "+f"(d[17]), "+f"(d[18]), "+f"(d[19]), "+f"(d[20]), "+f"(d[21]), "+f"(d[22]), "+f"(d[23]),
          "+f"(d[24]), "+f"(d[25]), "+f"(d[26]), "+f"(d[27]), "+f"(d[28]), "+f"(d[29]), "+f"(d[30]), "+f"(d[31])
        : "r"(a.x), "r"(a.y), "r"(a.z), "r"(a.w), "r"(descB));
}

__device__ __forceinline__ void wgmma_rs(float (&d)[16], const uint4& a, uint32_t descB) {
    asm volatile(
        "{\n.reg .pred p;\n.reg .b64 db;\nsetp.eq.b32 p, 0, 0;\n"
        "mov.b64 db, {%20, 0x10};\n"
        "wgmma.mma_async.sync.aligned.m64n32k16.f32.bf16.bf16 "
        "{%0, %1, %2, %3, %4, %5, %6, %7, %8, %9, %10, %11, %12, %13, %14, %15}, "
        "{%16, %17, %18, %19}, db, p, 1, 1, 1;\n}\n"
        : "+f"(d[0]), "+f"(d[1]), "+f"(d[2]), "+f"(d[3]), "+f"(d[4]), "+f"(d[5]), "+f"(d[6]), "+f"(d[7]),
          "+f"(d[8]), "+f"(d[9]), "+f"(d[10]), "+f"(d[11]), "+f"(d[12]), "+f"(d[13]), "+f"(d[14]), "+f"(d[15])
        : "r"(a.x), "r"(a.y), "r"(a.z), "r"(a.w), "r"(descB));
}

#define XL 0
#define DLY1 0
#define FAST 0
#define GAP 60
#define W3U 4
#define S4U 3
#define S4W 0
#define S4L 0
#define X3P 0
#define S1P 1
#define S3U 1
#define S3L 0
#define GDUR {448,448,448,448,448,448, 448,448,448,448,448,448,448,448,448,448,448,448,448,448,448,448}
#define TW 2
#define NRS 4
#define C0E 1
#define SS 0
#define WS 1
#define PFX 1
#define PFA 2
#define S2P 1
#define DLY2 300
#define TM(i) TC(i)
#define TD(i)
__device__ __forceinline__ uint32_t pack8x(const uint4& a, const uint4& b) {
    return madi(madi(madi(b.w, 65536, a.w), 16, madi(b.z, 65536, a.z)), 256, madi(madi(b.y, 65536, a.y), 16, madi(b.x, 65536, a.x)));
}
constexpr int NT = N_ / BN, MT = M_ / BM;
constexpr int W_BYTES = BN * BK * 2;
constexpr int X_OFF = 0;
constexpr int W_OFF = 81920;
constexpr int R_OFF = W_OFF + 4 * W_BYTES;
constexpr int SC_OFF = R_OFF + W_BYTES - 2 * 448;
constexpr int RAW0_OFF = W_OFF + 2 * W_BYTES;
constexpr int SC0_OFF = W_OFF + 3 * W_BYTES;
constexpr int BAR_OFF = SC_OFF + 16 * 448;
constexpr int TC_OFF = BAR_OFF + 576;
constexpr int SMEM_BYTES = BAR_OFF + 896;
constexpr unsigned READY = MT * 7;
constexpr int UM = 22;
constexpr int NAG = 6;

__device__ __align__(1024) uint8_t g_wimg[(size_t)NT * KC * W_BYTES];
__device__ unsigned g_flag[NT * 32];

template <int NR>
__device__ __forceinline__ void store_cols(const float (&acc)[NR], int j0, int j1, uint8_t* p) {
#pragma unroll
    for (int j = j0; j < j1; j++) {
        const int i = 16 * j;
        stg128(p + j * 64, pack_bf16(acc[i], acc[i + 1]), pack_bf16(acc[i + 4], acc[i + 5]), pack_bf16(acc[i + 8], acc[i + 9]), pack_bf16(acc[i + 12], acc[i + 13]));
        stg128(p + j * 64 + 8 * N_ * 2, pack_bf16(acc[i + 2], acc[i + 3]), pack_bf16(acc[i + 6], acc[i + 7]), pack_bf16(acc[i + 10], acc[i + 11]), pack_bf16(acc[i + 14], acc[i + 15]));
    }
}

__host__ __device__ constexpr int slab_at(int u) {
    return u == 0 ? 2 : u == S3U ? 3 : u == S4U ? 4 : u == 5 ? 5 : u == (SS ? 6 : 7) ? 6 : (u >= 8 && u <= 16) ? u - 1 : -1;
}
__host__ __device__ constexpr int wload_at(int u) {
    return u == 2 ? 2 : u == W3U ? 3 : u == 5 + WS ? 4 : u == 7 + WS ? 5 : u == 9 + WS ? 6 : u == 12 ? 7 : u == 13 ? 8 : u == 15 ? 9 : u == 17 ? 10
         : u == 18 ? 11 : u == 19 ? 12 : u == 20 ? 15 : u == 21 ? 13 : -1;
}
__host__ __device__ constexpr int xslot(int u) { return u % 5; }
__host__ __device__ constexpr int xpar(int u) { return (u / 5) & 1; }
__host__ __device__ constexpr int tail_chunk(int j) { return j == 3 ? 15 : j == 4 ? 14 : 11 + j; }
__host__ __device__ constexpr int wbuf(int c) { return c == 15 ? 4 : c & 3; }

__global__ void __cluster_dims__(2, 1, 1) __launch_bounds__(256, 1)
nf4_gemm_kernel(const uint8_t* __restrict__ qw, const __nv_bfloat16* __restrict__ cb, const __nv_bfloat16* __restrict__ absmax, uint8_t* __restrict__ wimg,
                unsigned* __restrict__ gflags, uint8_t* __restrict__ out, const unsigned zero, const __grid_constant__ CUtensorMap tmx,
                const __grid_constant__ CUtensorMap tmx64, const __grid_constant__ CUtensorMap tmq, const __grid_constant__ CUtensorMap tmq7,
                const __grid_constant__ CUtensorMap tmq1, const __grid_constant__ CUtensorMap tms) {
    extern __shared__ __align__(1024) uint8_t smem[];
    TS_FIRST();
    const int rank = blockIdx.x & 1;
    const int mt = (blockIdx.x >> 5) * 2 + rank, nt = (blockIdx.x >> 1) & 15;
    asm volatile(
        "{\n.reg .b32 t, b, o, h;\n.reg .b64 a;\n"
        "mov.u32 t, %%tid.x;\nmov.u32 b, %%ctaid.x;\n"
        "shr.u32 h, t, 5;\nshl.b32 o, t, 5;\nmad.lo.u32 o, h, %1 - 1024, o;\n"
        "and.b32 h, b, 1;\nmad.lo.u32 o, h, 8 * %1 - %2 / 2, o;\n"
        "shr.u32 h, b, 5;\nmad.lo.u32 o, h, 16 * %1 - 16 * %2, o;\n"
        "mad.lo.u32 o, b, %2 / 2, o;\n"
        "cvt.u64.u32 a, o;\nadd.u64 a, a, %0;\n"
        "prefetch.global.L2 [a];\n"
        "}\n" ::"l"(qw), "n"(N_ * 4), "n"(BN * 4));
    const uint32_t sbase = smem_u32(smem);
    const int warp = __shfl_sync(~0u, (int)(threadIdx.x >> 5), 0);
    const int wg = warp >> 2, wj = warp & 3;
    const int lane = threadIdx.x & 31;
    const uint32_t bars = sbase + BAR_OFF;
    const uint32_t snap = bars;
    const uint32_t xfull = bars + 64 + wg * 40;
    const uint32_t wfull = bars + 144;
    const uint32_t wempty = bars + 184;
    const uint32_t ringfull = bars + 216;
    const uint32_t rawbar = bars + 248;
    const uint32_t wown = bars + 264;
    const uint32_t stored = bars + 272 - 8;
    const uint32_t xbase = sbase + X_OFF + wg * 40960, wbase = sbase + W_OFF, rbase = sbase + R_OFF;
    const int xrow = mt * BM + wg * 128 + wj * 16;
    const uint8_t* wsrc = wimg + (size_t)nt * KC * W_BYTES;
    unsigned* flags = gflags + nt * 32;
    TS_INIT();

    auto load_slab7 = [&](int c, uint32_t extra = 0) {
        mbar_expect_tx(ringfull + 8 * (c & 3), 7168 + extra);
        tma_load_3d(rbase + (c & 3) * 7168, &tmq7, 0, c * BK + mt * 8, nt * 7, ringfull + 8 * (c & 3));
    };
    auto load_x = [&](int u, int cs = -1, uint32_t bytes = 2048) {
        const int c = u < UM ? u >> 1 : tail_chunk((u - UM) % 5), b = u < UM ? u & 1 : (u - UM) / 5;
        mbar_expect_tx(xfull + 8 * xslot(u), bytes);
        tma_load_2d(xbase + xslot(u) * 8192 + wj * 2048, &tmx, c * BK, xrow + b * 64, xfull + 8 * xslot(u));
        if (cs >= 0) tma_load_2d(rbase + (cs & 3) * 7168 + warp * 1024, &tmq1, nt * BN + warp * 32, cs * BK + mt * 8, xfull + 8 * xslot(u));
    };
    auto load_x64 = [&](int g, int u) {
        const uint32_t bar = bars + 64 + g * 40 + 8 * u;
        mbar_arrive_n(bar, 3);
        mbar_expect_tx(bar, 8192);
        tma_load_2d(sbase + X_OFF + g * 40960 + u * 8192, &tmx64, (u >> 1) * BK, mt * BM + g * 128 + (u & 1) * 64, bar);
    };
    auto load_raw = [&](int p, uint32_t extra) {
        mbar_expect_tx(rawbar + 8 * p, 14336 + extra);
        tma_load_3d(sbase + RAW0_OFF + p * 14336, &tmq, 0, rank * 32 + p * 16, nt * 7, rawbar + 8 * p);
    };
    auto prefetch_x = [&](int c) { if (PFX && c < KC) tma_prefetch_2d(&tmx, c * BK, mt * BM + nt * 16); };
    auto load_x23 = [&]() { load_x64(0, 2); load_x64(1, 2); load_x64(0, 3); load_x64(1, 3); };
    auto load_slab2 = [&]() {
        load_slab7(2, 14 * 448);
        tma_load_2d(sbase + SC_OFF + 2 * 448, &tms, nt * BN, 2, ringfull + 16);
    };
    if (warp == 7) {
        if (elect()) {
            mbar_init(ringfull + 8, 1); mbar_init(rawbar, 1); mbar_init(rawbar + 8, 1);
            auto slab1 = [&]() { load_slab7(1, 448); bulk_load(sbase + SC0_OFF + 448, absmax + N_ + nt * BN, 448, ringfull + 8); };
            if (S1P == 0) slab1();
            load_raw(0, 448);
            bulk_load(sbase + SC0_OFF, absmax + nt * BN, 448, rawbar);
            if (S1P == 1) slab1();
            load_raw(1, 0);
            if (S1P == 2) slab1();
            mbar_init(bars + 64, 4); mbar_init(bars + 72, 4); mbar_init(bars + 104, 4); mbar_init(bars + 112, 4); mbar_init(ringfull + 16, 1);
            asm volatile("fence.mbarrier_init.release.cluster;" ::: "memory");
        }
        __syncwarp();
    }
    uint4 c0, c1;
    asm volatile("ld.global.nc.v4.u32 {%0, %1, %2, %3}, [%8];\nld.global.nc.v4.u32 {%4, %5, %6, %7}, [%8 + 16];"
                 : "=r"(c0.x), "=r"(c0.y), "=r"(c0.z), "=r"(c0.w), "=r"(c1.x), "=r"(c1.y), "=r"(c1.z), "=r"(c1.w) : "l"(cb));
    if (warp == 5 || warp == 6) {
        if (elect()) {
            if (warp == 6) {
#pragma unroll
                for (int s = 0; s < 5; s++) mbar_init(wfull + 8 * s, 1);
#pragma unroll
                for (int s = 0; s < 4; s++) mbar_init(wempty + 8 * s, 16);
                mbar_init(wown, 7); mbar_init(ringfull, 1); mbar_init(ringfull + 24, 1);
                mbar_expect_tx(wfull, W_BYTES / 2);
            }
            if (warp == 5) {
#pragma unroll
                for (int s = 0; s < 10; s++) if (s % 5 >= 2) mbar_init(bars + 64 + 8 * s, 4);
#pragma unroll
                for (int s = 1; s <= NAG; s++) mbar_init(stored + 8 * s, 224);
            }
            asm volatile("fence.mbarrier_init.release.cluster;" ::: "memory");
        }
        __syncwarp();
    }
    cluster_arrive();
    if (warp == 7) {
        if (elect()) {
            load_x64(0, 0); load_x64(0, 1); load_x64(1, 0); load_x64(1, 1);
        }
        __syncwarp();
    }
    const uint32_t rlane = (lane & 7) * 128 + ((((lane >> 3) * 2) ^ (lane & 7)) << 4);
    const uint32_t wlane = warp * 1024 + (lane & 7) * 16 + (lane >> 3) * 4;
    const uint32_t slabsrc = __shfl_sync(~0u, (warp < 7 ? warp * 1024 + rlane : 0) + sbase, lane);
    const uint32_t scsrc = __shfl_sync(~0u, sbase + (warp < 7 ? warp * 64 : 0) + (lane >> 3) * 16, lane);
    uint8_t* const gdst = wimg + (size_t)nt * KC * W_BYTES + (mt >> 1) * 7168 + (mt & 1) * 128 + wlane;
    uint8_t* const gkeep = (uint8_t*)__shfl_sync(~0u, (unsigned long long)gdst, lane);
    uint8_t* const gprobe = (uint8_t*)__shfl_sync(~0u, (unsigned long long)(warp < 7 ? gdst + (lane >> 3) * 252 : (uint8_t*)flags + (lane >> 3) * 16), lane);
    Lut lut = {};
    if (warp < 7) {
        lut.lo[0] = __byte_perm(c0.x, c0.y, 0x6420); lut.hi[0] = __byte_perm(c0.x, c0.y, 0x7531);
        lut.lo[1] = __byte_perm(c0.z, c0.w, 0x6420); lut.hi[1] = __byte_perm(c0.z, c0.w, 0x7531);
        lut.lo[2] = __byte_perm(c1.x, c1.y, 0x6420); lut.hi[2] = __byte_perm(c1.x, c1.y, 0x7531);
        lut.lo[3] = __byte_perm(c1.z, c1.w, 0x6420); lut.hi[3] = __byte_perm(c1.z, c1.w, 0x7531);
    }
    cluster_wait();
    auto store_slab = [&](int c, uint32_t p, const uint4& sc) {
        const uint4 w = dequant8p(p, sc, lut);
        uint8_t* g = gkeep + (size_t)c * W_BYTES;
        stg32(g, w.x); stg32(g + 256, w.y); stg32(g + 512, w.z); stg32(g + 768, w.w);
        probe_l2(scsrc + (c < 2 ? SC0_OFF : SC_OFF) + 448 * c, gprobe + (size_t)c * W_BYTES, (lane & 7) == 0);
        if (c <= NAG) probe_arrive(stored + 8 * c);
    };
    auto take_sample = [&]() { probe_l2(scsrc + BAR_OFF, gprobe, (lane & 7) == 0); };
    auto count_slab = [&](int c) {
        mbar_wait(stored + 8 * c, 0);
        if (elect()) red_add(flags + c, 7);
        __syncwarp();
    };
    auto load_w = [&](int c, bool fast = false) {
        if (fast) poll_fast(flags + (c & ~3), c & 3, bars + 336, READY, GAP);
        else {
            probe_wait<0>(); __syncwarp();
            poll_ge(flags + c, lds32(snap + 4 * c), READY);
        }
        asm volatile("fence.acquire.gpu;" ::: "memory");
        asm volatile("fence.proxy.async.global;" ::: "memory");
        if (c >= 4 && c < 15) mbar_wait(wempty + 8 * (c & 3), ((c >> 2) - 1) & 1);
        if (elect()) {
            mbar_expect_tx(wfull + 8 * wbuf(c), W_BYTES);
            bulk_load_mc(wbase + wbuf(c) * W_BYTES + rank * (W_BYTES / 2), wsrc + (size_t)c * W_BYTES + rank * (W_BYTES / 2), W_BYTES / 2, wfull + 8 * wbuf(c));
        }
        __syncwarp();
    };
    if (warp < 7) {
        auto slab1 = [&]() {
            mbar_wait(ringfull + 8, 0);
            TC(5);
            store_slab(1, pack8x(lds128(slabsrc + R_OFF + 7168), lds128((slabsrc ^ 16) + R_OFF + 7168)), lds128(scsrc + SC0_OFF + 448));
        };
        if (S1P == 0) slab1();
        const uint32_t d = wbase + rank * 14336;
        uint4 sc;
#pragma unroll
        for (int p = 0; p < 2; p++) {
            mbar_wait(rawbar + 8 * p, 0);
            if (p == 0) { TC(7); sc = lds128(scsrc + SC0_OFF); }
            const uint32_t a = sbase + RAW0_OFF + p * 14336 + warp * 2048;
            uint32_t p1, p2;
            pack16(lds128(a + rlane), lds128(a + (rlane ^ 16)), lds128(a + rlane + 1024), lds128(a + (rlane ^ 16) + 1024), p1, p2);
            const uint4 w0 = dequant16<0>(p1, p2, sc, lut), w1 = dequant16<1>(p1, p2, sc, lut);
            const uint32_t e = d + p * 7168 + wlane;
            sts32(e, w0.x); sts32(e + 256, w0.y); sts32(e + 512, w0.z); sts32(e + 768, w0.w);
            sts32(e + 128, w1.x); sts32(e + 384, w1.y); sts32(e + 640, w1.z); sts32(e + 896, w1.w);
            if (p == 1 || C0E) {
                fence_async_smem();
                __syncwarp();
                if (elect()) {
                    if (p == 1) mbar_arrive(wown);
                    if (!C0E) copy_to_peer(d + warp * 1024, 1024, wfull, rank ^ 1);
                    copy_to_peer(d + p * 7168 + warp * 1024, 1024, wfull, rank ^ 1);
                }
                __syncwarp();
            }
            if (S1P == p + 1) slab1();
        }
        TC(6);
    } else {
        mbar_wait(rawbar, 0);
        if (elect()) { load_slab2(); prefetch_x(1); }
        __syncwarp();
        if (XL == 1 || S3L == 1) {
            mbar_wait(ringfull + 8, 0);
            if (elect()) { if (XL == 1) load_x23(); if (S3L == 1) load_slab7(3); }
            __syncwarp();
        }
        count_slab(1);
        TC(5);
        if (elect()) { if (XL == 0) load_x23(); if (S3L == 0) load_slab7(3); }
        __syncwarp();
        if (DLY1) { delay(DLY1); take_sample(); }
    }

    float acc0[112], acc1[112];
    const uint32_t descA = ((xbase & 0x3FFFF) >> 4) | (1u << 16), descB = ((wbase & 0x3FFFF) >> 4) | ((128u >> 4) << 16);
    static_for<0, UM>([&](auto U) __attribute__((always_inline)) {
        constexpr int u = U.value, kc = u >> 1;
        uint32_t da = descA, db = descB;
        asm volatile("" : "+r"(da), "+r"(db));
        uint4 q0, q1, sc;
        constexpr int c = slab_at(u);
        auto slab_loads = [&]() {
            q0 = lds128(slabsrc + R_OFF + (c & 3) * 7168); q1 = lds128((slabsrc ^ 16) + R_OFF + (c & 3) * 7168);
            sc = lds128(scsrc + SC_OFF + 448 * c);
        };
        if (u < 2) {
            if (u == 0) mbar_wait3(xfull, 0, xfull + 8, 0, wown, 0);
            else mbar_wait(wfull, 0);
            if (u == 0 && !DLY1 && warp == 7) take_sample();
            TM(8 + 3 * u);
            const int h = rank ^ u;
            da += h * 4; db += h * (14336 >> 4);
            wgmma_fence();
            wgmma_ss<u>(acc0, da, db); wgmma_ss<u>(acc1, da + 512, db);
            wgmma_ss<1>(acc0, da + 2, db + (7168 >> 4)); wgmma_ss<1>(acc1, da + 514, db + (7168 >> 4));
        } else {
            da += xslot(u) * 512; db += (kc & 3) * (W_BYTES >> 4);
            if (c == 3) mbar_wait3(xfull + 8 * xslot(u), xpar(u), wfull + 8, 0, ringfull + 24, 0);
            else if (c == 4 && u == 3 && !S4W) mbar_wait2(xfull + 8 * xslot(u), xpar(u), ringfull, 0);
            else if (c == 4 && u == 4) mbar_wait3(xfull + 8 * xslot(u), xpar(u), wfull + 16, 0, ringfull, 0);
            else if (u & 1) mbar_wait(xfull + 8 * xslot(u), xpar(u));
            else mbar_wait2(xfull + 8 * xslot(u), xpar(u), wfull + 8 * (kc & 3), (kc >> 2) & 1);
            if (c >= 0 && !(u == 3 && S4W)) slab_loads();
            TM(8 + 3 * u);
            wgmma_fence();
#pragma unroll
            for (int ks = 0; ks < 4; ks++) {
                if (u & 1) wgmma_ss<1>(acc1, da + ks * 2, db + ks * (7168 >> 4));
                else wgmma_ss<1>(acc0, da + ks * 2, db + ks * (7168 >> 4));
            }
        }
        wgmma_commit(); TG(u);
        if (u >= 2) wgmma_wait<1>();
        TM(9 + 3 * u);
        if (warp < 7) {
            if ((u < 2 || (u == 3 && S4W)) && c >= 0) { mbar_wait(ringfull + 8 * (c & 3), 0); slab_loads(); }
            constexpr int cp = slab_at(u - 2) > NAG ? slab_at(u - 2) : -1;
            uint32_t p = 0;
            if (c >= 0) p = pack8x(q0, q1);
            if (cp >= 0) { if (slab_at(u - 1) >= 0) probe_wait<1>(); else probe_wait<0>(); __syncwarp(); }
            if (u >= 2) {
                if (elect()) {
                    if (u == 2) load_x(5, slab_at(5), 3072);
                    load_x(u + 4, slab_at(u + 4), slab_at(u + 4) >= 0 ? after(3072, p, zero) : 2048);
                    if (!(u & 1)) mbar_arrive_both(wempty + 8 * ((kc - 1) & 3));
                    if (cp >= 0) red_add(flags + cp, 1);
                }
                __syncwarp();
            }
            if (c >= 0) store_slab(c, p, sc);
        } else {
            if (u == 0) {
                if (XL == 2 || S3L == 2) { if (elect()) { if (XL == 2) load_x23(); if (S3L == 2) load_slab7(3); } __syncwarp(); }
                load_w(1, FAST & 1);
                if (elect()) { if (S3L == 3) load_slab7(3); prefetch_x(2); if (S4L == 0) load_slab7(4); }
                __syncwarp();
            } else if (u == 1) {
                if (S4L == 1) { if (elect()) load_slab7(4); __syncwarp(); }
                count_slab(2);
                if (elect()) { load_x64(0, 4); load_x64(1, 4); if (S4L == 2) load_slab7(4); prefetch_x(3); }
                __syncwarp();
                if (FAST & 2) load_w(2, true);
                else if (DLY2) delay(DLY2);
            } else {
                if (u == 2 && !(FAST & 2)) load_w(2);
                if (elect()) {
                    if (u == 2) load_x(5);
                    load_x(u + 4);
                    if (!(u & 1)) mbar_arrive_both(wempty + 8 * ((kc - 1) & 3));
                    prefetch_x(u + 2);
                }
                __syncwarp();
                if (slab_at(u - 1) >= 0 && slab_at(u - 1) <= NAG) count_slab(slab_at(u - 1));
                if (u > 2 && wload_at(u) >= 0) load_w(wload_at(u));
            }
            if (u + 1 < UM && wload_at(u + 1) >= 0 && !(u == 1 && (FAST & 2))) take_sample();
        }
        TM(10 + 3 * u);
    });
    uint32_t tA = descA, tB = descB;
    asm volatile("" : "+r"(tA), "+r"(tB));
    if (wg == 1) {
        wgmma_wait<0>();
        if (elect()) { load_x(UM + 4); mbar_arrive_both(wempty + 16); }
        __syncwarp();
        if (warp == 7) load_w(14);
    if (warp == 7 && lane == 0) {
        if (atomicAdd(flags + 16, 1) == MT - 1) {
#pragma unroll
            for (int c = 0; c <= 16; c++) flags[c] = 0;
        }
    }
    __syncwarp();
        bar_sync<256>(1);
    }
    TC(74);
#pragma unroll
    for (int j = 0; j < 5; j++) {
        const int c = tail_chunk(j), v = UM + j;
        mbar_wait2(xfull + 8 * xslot(v), xpar(v), wfull + 8 * wbuf(c), c == 15 ? 0 : (c >> 2) & 1);
        wgmma_fence();
#pragma unroll
        for (int ks = 0; ks < 4; ks++) wgmma_ss<1>(acc0, tA + xslot(v) * 512 + ks * 2, tB + wbuf(c) * (W_BYTES >> 4) + ks * (7168 >> 4));
        wgmma_commit();
        if (j == 4) bar_arrive<256>(1 + wg);
        if (j == 0) {
            if (wg == 0) {
                wgmma_wait<1>();
                if (elect()) { load_x(UM + 4); mbar_arrive_both(wempty + 16); }
                __syncwarp();
            }
        } else if (TW == 1) {
            wgmma_wait<1>();
            if (elect()) load_x(v + 4);
            __syncwarp();
        } else if (j >= 2) {
            wgmma_wait<2>();
            if (elect()) load_x(v + 3);
            __syncwarp();
        }
    }
    if (TW == 2) {
        wgmma_wait<1>();
        if (elect()) load_x(UM + 8);
        __syncwarp();
    }
    wgmma_wait<0>();
    TC(75);
    if (elect()) load_x(UM + 9);
    __syncwarp();
    uint8_t* optr = out + (size_t)(xrow + (lane >> 2)) * (N_ * 2) + nt * (BN * 2) + (lane & 3) * 16;
#define NA 4
#define NB 2
#define LEFT0 4
#define LEFT1 1
    constexpr int NC = 7 - NA - NB;
    float pa[16 * NA], pb[16 * NB], pc[16 * NC];
#pragma unroll
    for (int i = 0; i < 16 * NA; i++) asm volatile("mov.b32 %0, %1;" : "=f"(pa[i]) : "f"(acc1[i]));
#pragma unroll
    for (int i = 0; i < 16 * NB; i++) asm volatile("mov.b32 %0, %1;" : "=f"(pb[i]) : "f"(acc1[16 * NA + i]));
#pragma unroll
    for (int i = 0; i < 16 * NC; i++) asm volatile("mov.b32 %0, %1;" : "=f"(pc[i]) : "f"(acc1[16 * (NA + NB) + i]));
    uint4 af[4 * NRS];
    uint32_t pk[56];
#pragma unroll
    for (int i = 0; i < 56; i++) pk[i] = pack_bf16(acc0[2 * i], acc0[2 * i + 1]);
    auto store_pk = [&](int h) {
        const int i = 8 * (h >> 1) + (h & 1);
        stg128(optr + (h >> 1) * 64 + (h & 1) * (8 * N_ * 2), pk[i], pk[i + 2], pk[i + 4], pk[i + 6]);
    };
    {
        const uint32_t alane = xbase + wj * 2048 + (lane & 15) * 128 + (((lane >> 4) ^ (lane & 7)) << 4);
        store_pk(0); store_pk(1);
#pragma unroll
        for (int j = 0; j < NRS; j++) {
            const int v = UM + 5 + j;
            mbar_wait(xfull + 8 * xslot(v), xpar(v));
#pragma unroll
            for (int ks = 0; ks < 4; ks++) af[4 * j + ks] = ldmatrix_x4((alane ^ (ks * 32)) + xslot(v) * 8192);
#pragma unroll
            for (int h = 2; h < 14; h++) if (h >= 2 + j * (12 - 2 * LEFT0) / NRS && h < 2 + (j + 1) * (12 - 2 * LEFT0) / NRS) store_pk(h);
        }
    }
    if (wg == 0) {
#pragma unroll
        for (int h = 14 - 2 * LEFT0; h < 14; h++) store_pk(h);
    }
#pragma unroll
    for (int j = NRS; j < 5; j++) mbar_wait(xfull + 8 * xslot(UM + 5 + j), xpar(UM + 5 + j));
    TC(76);
    auto piece = [&](auto& d, int cb) {
        wgmma_fence();
#pragma unroll
        for (int j = 0; j < 5; j++)
#pragma unroll
            for (int ks = 0; ks < 4; ks++) {
                const uint32_t db = tB + wbuf(tail_chunk(j)) * (W_BYTES >> 4) + ks * (7168 >> 4) + cb * 64;
                if (j < NRS) wgmma_rs(d, af[j < NRS ? 4 * j + ks : 0], db);
                else wgmma_ss<1>(d, tA + xslot(UM + 5 + j) * 512 + ks * 2, db);
            }
        wgmma_commit();
    };
    bar_sync<256>(2 + wg);
    TC(77);
    piece(pa, 0);
    bar_arrive<256>(3 + wg);
    if (wg == 1) {
#pragma unroll
        for (int h = 14 - 2 * LEFT0; h < 14; h++) store_pk(h);
    }
    wgmma_wait<0>();
    TC(78);
    optr += 64 * N_ * 2;
    store_cols(pa, 0, NA - LEFT1, optr);
    if (wg == 0) store_cols(pa, NA - LEFT1, NA, optr);
    TC(79);
    bar_sync<256>(4 + wg);
    piece(pb, NA);
    bar_arrive<256>(5 + wg);
    if (wg == 1) store_cols(pa, NA - LEFT1, NA, optr);
    wgmma_wait<0>();
    TC(2);
    if (wg == 0) store_cols(pb, 0, NB, optr + NA * 64);
    bar_sync<256>(6 + wg);
    piece(pc, NA + NB);
    if (wg == 0) bar_arrive<256>(7);
    else store_cols(pb, 0, NB, optr + NA * 64);
    cluster_arrive();
    wgmma_wait<0>();
    TC(3);
    store_cols(pc, 0, NC, optr + (NA + NB) * 64);
    TC(4);
    TS_DUMP();
    cluster_wait();
}

typedef CUresult (*EncodeFn)(CUtensorMap*, CUtensorMapDataType, cuuint32_t, void*, const cuuint64_t*, const cuuint64_t*,
                             const cuuint32_t*, const cuuint32_t*, CUtensorMapInterleave, CUtensorMapSwizzle,
                             CUtensorMapL2promotion, CUtensorMapFloatOOBfill);

extern "C" void kernel_launch(void* const* d_in, const int* in_sizes, int n_in, void* d_out, int out_size) {
    const __nv_bfloat16* x = (const __nv_bfloat16*)d_in[0];
    const int* qw = (const int*)d_in[1];
    const __nv_bfloat16* cb = (const __nv_bfloat16*)d_in[2];
    const __nv_bfloat16* absmax = (const __nv_bfloat16*)d_in[3];
    static EncodeFn encode = nullptr;
    static void *wimg = nullptr, *gflags = nullptr;
    if (!encode) {
        cudaGetSymbolAddress(&wimg, g_wimg);
        cudaGetSymbolAddress(&gflags, g_flag);
        void* fn = nullptr;
        cudaDriverEntryPointQueryResult qr;
        cudaGetDriverEntryPoint("cuTensorMapEncodeTiled", &fn, cudaEnableDefault, &qr);
        encode = (EncodeFn)fn;
        cudaFuncSetAttribute(nf4_gemm_kernel, cudaFuncAttributeMaxDynamicSharedMemorySize, SMEM_BYTES);
    }
    CUtensorMap tmx, tmx64, tmq, tmq7, tmq1, tms;
    const cuuint32_t es[3] = {1, 1, 1};
    {
        cuuint64_t dims[2] = {(cuuint64_t)K_, (cuuint64_t)M_};
        cuuint64_t strides[1] = {(cuuint64_t)K_ * 2};
        cuuint32_t box[2] = {64, 16};
        encode(&tmx, CU_TENSOR_MAP_DATA_TYPE_BFLOAT16, 2, (void*)x, dims, strides, box, es, CU_TENSOR_MAP_INTERLEAVE_NONE,
               CU_TENSOR_MAP_SWIZZLE_128B, CU_TENSOR_MAP_L2_PROMOTION_L2_128B, CU_TENSOR_MAP_FLOAT_OOB_FILL_NONE);
        box[1] = 64;
        encode(&tmx64, CU_TENSOR_MAP_DATA_TYPE_BFLOAT16, 2, (void*)x, dims, strides, box, es, CU_TENSOR_MAP_INTERLEAVE_NONE,
               CU_TENSOR_MAP_SWIZZLE_128B, CU_TENSOR_MAP_L2_PROMOTION_L2_128B, CU_TENSOR_MAP_FLOAT_OOB_FILL_NONE);
    }
    {
        cuuint64_t dims[3] = {32, (cuuint64_t)K_, (cuuint64_t)(N_ / 32)};
        cuuint64_t strides[2] = {(cuuint64_t)N_ * 4, 128};
        cuuint32_t box[3] = {32, 16, 7};
        encode(&tmq, CU_TENSOR_MAP_DATA_TYPE_INT32, 3, (void*)qw, dims, strides, box, es, CU_TENSOR_MAP_INTERLEAVE_NONE,
               CU_TENSOR_MAP_SWIZZLE_128B, CU_TENSOR_MAP_L2_PROMOTION_L2_128B, CU_TENSOR_MAP_FLOAT_OOB_FILL_NONE);
        box[1] = 8;
        encode(&tmq7, CU_TENSOR_MAP_DATA_TYPE_INT32, 3, (void*)qw, dims, strides, box, es, CU_TENSOR_MAP_INTERLEAVE_NONE,
               CU_TENSOR_MAP_SWIZZLE_128B, CU_TENSOR_MAP_L2_PROMOTION_L2_128B, CU_TENSOR_MAP_FLOAT_OOB_FILL_NONE);
    }
    {
        cuuint64_t dims[2] = {(cuuint64_t)N_, (cuuint64_t)K_};
        cuuint64_t strides[1] = {(cuuint64_t)N_ * 4};
        cuuint32_t box[2] = {32, 8};
        encode(&tmq1, CU_TENSOR_MAP_DATA_TYPE_INT32, 2, (void*)qw, dims, strides, box, es, CU_TENSOR_MAP_INTERLEAVE_NONE,
               CU_TENSOR_MAP_SWIZZLE_128B, CU_TENSOR_MAP_L2_PROMOTION_L2_128B, CU_TENSOR_MAP_FLOAT_OOB_FILL_NONE);
    }
    {
        cuuint64_t dims[2] = {(cuuint64_t)N_, (cuuint64_t)KC};
        cuuint64_t strides[1] = {(cuuint64_t)N_ * 2};
        cuuint32_t box[2] = {BN, KC - 2};
        encode(&tms, CU_TENSOR_MAP_DATA_TYPE_BFLOAT16, 2, (void*)absmax, dims, strides, box, es, CU_TENSOR_MAP_INTERLEAVE_NONE,
               CU_TENSOR_MAP_SWIZZLE_NONE, CU_TENSOR_MAP_L2_PROMOTION_NONE, CU_TENSOR_MAP_FLOAT_OOB_FILL_NONE);
    }
    nf4_gemm_kernel<<<128, 256, SMEM_BYTES>>>((const uint8_t*)qw, cb, absmax, (uint8_t*)wimg, (unsigned*)gflags, (uint8_t*)d_out, 0u, tmx, tmx64, tmq, tmq7, tmq1, tms);
}
```

```cpp
#include <cuda_runtime.h>
#include <cuda_bf16.h>
#include <cuda.h>
#include <stdint.h>

constexpr int M_ = 2048, K_ = 1024, N_ = 3584;
constexpr int BM = 256, BN = 224, BK = 64;
constexpr int KC = K_ / BK;

__device__ __forceinline__ uint32_t smem_u32(const void* p) { return (uint32_t)__cvta_generic_to_shared(p); }
__device__ __forceinline__ bool elect() {
    uint32_t ok;
    asm volatile("{\n.reg .pred p;\nelect.sync _|p, 0xffffffff;\nselp.u32 %0, 1, 0, p;\n}\n" : "=r"(ok));
    return ok != 0;
}
template <int I> struct IC { static constexpr int value = I; };
template <int I, int N, class F> __device__ __forceinline__ void static_for(F&& f) {
    if constexpr (I < N) { f(IC<I>{}); static_for<I + 1, N>(f); }
}

__device__ __forceinline__ void mbar_init(uint32_t bar, uint32_t cnt) { asm volatile("mbarrier.init.shared::cta.b64 [%0], %1;" ::"r"(bar), "r"(cnt) : "memory"); }
__device__ __forceinline__ void mbar_init_fence() { asm volatile("fence.mbarrier_init.release.cluster;" ::: "memory"); }
__device__ __forceinline__ void mbar_expect_tx(uint32_t bar, uint32_t bytes) { asm volatile("mbarrier.arrive.expect_tx.shared::cta.b64 _, [%0], %1;" ::"r"(bar), "r"(bytes) : "memory"); }
__device__ __forceinline__ void mbar_arrive(uint32_t bar) { asm volatile("mbarrier.arrive.shared::cta.b64 _, [%0];" ::"r"(bar) : "memory"); }
__device__ __forceinline__ void mbar_arrive_n(uint32_t bar, uint32_t n) { asm volatile("mbarrier.arrive.shared::cta.b64 _, [%0], %1;" ::"r"(bar), "r"(n) : "memory"); }
__device__ __forceinline__ void mbar_arrive_both(uint32_t bar) {
    asm volatile("{\n.reg .b32 ra;\nmapa.shared::cluster.u32 ra, %0, 0;\nmbarrier.arrive.shared::cluster.b64 _, [ra];\n"
                 "mapa.shared::cluster.u32 ra, %0, 1;\nmbarrier.arrive.shared::cluster.b64 _, [ra];\n}\n" ::"r"(bar) : "memory");
}
#define MBAR_TRY(p, b, q) "mbarrier.try_wait.parity.shared::cta.b64 " p ", [" b "], " q ";\n"
#define MBAR_WAIT(TRY) \
    "{\n.reg .pred p0, p1, p2;\n.reg .b32 n;\n" TRY "@p0 bra LAB_DONE;\nmov.b32 n, 0;\nLAB_WAIT:\n" TRY \
    "@p0 bra LAB_DONE;\nadd.u32 n, n, 1;\nsetp.lt.u32 p0, n, 0x40000;\n@p0 bra LAB_WAIT;\ntrap;\nLAB_DONE:\n}\n"
__device__ __forceinline__ void mbar_wait(uint32_t b0, uint32_t q0) {
    asm volatile(MBAR_WAIT(MBAR_TRY("p0", "%0", "%1")) ::"r"(b0), "r"(q0) : "memory");
}
__device__ __forceinline__ void mbar_wait2(uint32_t b0, uint32_t q0, uint32_t b1, uint32_t q1) {
    asm volatile(MBAR_WAIT(MBAR_TRY("p0", "%0", "%1") MBAR_TRY("p1", "%2", "%3") "and.pred p0, p0, p1;\n")
                 ::"r"(b0), "r"(q0), "r"(b1), "r"(q1) : "memory");
}
__device__ __forceinline__ void mbar_wait3(uint32_t b0, uint32_t q0, uint32_t b1, uint32_t q1, uint32_t b2, uint32_t q2) {
    asm volatile(MBAR_WAIT(MBAR_TRY("p0", "%0", "%1") MBAR_TRY("p1", "%2", "%3") MBAR_TRY("p2", "%4", "%5") "and.pred p0, p0, p1;\nand.pred p0, p0, p2;\n")
                 ::"r"(b0), "r"(q0), "r"(b1), "r"(q1), "r"(b2), "r"(q2) : "memory");
}
__device__ __forceinline__ void cluster_arrive() { asm volatile("barrier.cluster.arrive.relaxed.aligned;" ::: "memory"); }
__device__ __forceinline__ void cluster_wait() { asm volatile("barrier.cluster.wait.acquire.aligned;" ::: "memory"); }
template <int NTHR> __device__ __forceinline__ void bar_arrive(int id) { asm volatile("bar.arrive %0, %1;" ::"r"(id), "n"(NTHR) : "memory"); }
template <int NTHR> __device__ __forceinline__ void bar_sync(int id) { asm volatile("bar.sync %0, %1;" ::"r"(id), "n"(NTHR) : "memory"); }
__device__ __forceinline__ void delay(unsigned clks) {
    asm volatile(
        "{\n.reg .pred p;\n.reg .b32 t0, t;\n"
        "mov.u32 t0, %%clock;\n"
        "LAB_DELAY:\n"
        "mov.u32 t, %%clock;\n"
        "sub.u32 t, t, t0;\n"
        "setp.lt.u32 p, t, %0;\n"
        "vote.sync.any.pred p, p, 0xffffffff;\n"
        "@p bra.uni LAB_DELAY;\n}\n" ::"r"(clks) : "memory");
}

__device__ __forceinline__ void tma_load_2d(uint32_t dst, const CUtensorMap* tm, int c0, int c1, uint32_t bar) {
    asm volatile("cp.async.bulk.tensor.2d.shared::cluster.global.mbarrier::complete_tx::bytes [%0], [%1, {%2, %3}], [%4];"
                 ::"r"(dst), "l"(tm), "r"(c0), "r"(c1), "r"(bar) : "memory");
}
__device__ __forceinline__ void tma_load_3d(uint32_t dst, const CUtensorMap* tm, int c0, int c1, int c2, uint32_t bar) {
    asm volatile("cp.async.bulk.tensor.3d.shared::cluster.global.mbarrier::complete_tx::bytes [%0], [%1, {%2, %3, %4}], [%5];"
                 ::"r"(dst), "l"(tm), "r"(c0), "r"(c1), "r"(c2), "r"(bar) : "memory");
}
__device__ __forceinline__ void bulk_load(uint32_t dst, const void* src, uint32_t bytes, uint32_t bar) {
    asm volatile("cp.async.bulk.shared::cluster.global.mbarrier::complete_tx::bytes [%0], [%1], %2, [%3];"
                 ::"r"(dst), "l"(src), "r"(bytes), "r"(bar) : "memory");
}
__device__ __forceinline__ void bulk_load_mc(uint32_t dst, const void* src, uint32_t bytes, uint32_t bar) {
    asm volatile("cp.async.bulk.shared::cluster.global.mbarrier::complete_tx::bytes.multicast::cluster [%0], [%1], %2, [%3], %4;"
                 ::"r"(dst), "l"(src), "r"(bytes), "r"(bar), "h"((uint16_t)3) : "memory");
}
__device__ __forceinline__ uint32_t mapa(uint32_t addr, uint32_t cta) {
    uint32_t r; asm("mapa.shared::cluster.u32 %0, %1, %2;" : "=r"(r) : "r"(addr), "r"(cta)); return r;
}
__device__ __forceinline__ void copy_to_peer(uint32_t addr, uint32_t bytes, uint32_t bar, uint32_t peer) {
    asm volatile("cp.async.bulk.shared::cluster.shared::cta.mbarrier::complete_tx::bytes [%0], [%1], %2, [%3];"
                 ::"r"(mapa(addr, peer)), "r"(addr), "r"(bytes), "r"(mapa(bar, peer)) : "memory");
}
__device__ __forceinline__ void fence_async_smem() { asm volatile("fence.proxy.async.shared::cta;" ::: "memory"); }

__device__ __forceinline__ uint4 lds128(uint32_t a) {
    uint4 v; asm volatile("ld.shared.v4.b32 {%0, %1, %2, %3}, [%4];" : "=r"(v.x), "=r"(v.y), "=r"(v.z), "=r"(v.w) : "r"(a) : "memory"); return v;
}
__device__ __forceinline__ uint32_t lds32(uint32_t a) {
    uint32_t v; asm volatile("ld.shared.b32 %0, [%1];" : "=r"(v) : "r"(a) : "memory"); return v;
}
__device__ __forceinline__ uint4 ldmatrix_x4(uint32_t a) {
    uint4 v;
    asm volatile("ldmatrix.sync.aligned.m8n8.x4.shared.b16 {%0, %1, %2, %3}, [%4];" : "=r"(v.x), "=r"(v.y), "=r"(v.z), "=r"(v.w) : "r"(a) : "memory");
    return v;
}
__device__ __forceinline__ void sts32(uint32_t a, uint32_t v) { asm volatile("st.shared.b32 [%0], %1;" ::"r"(a), "r"(v) : "memory"); }
__device__ __forceinline__ void stg32(void* p, uint32_t v) { asm volatile("st.global.b32 [%0], %1;" ::"l"(p), "r"(v) : "memory"); }
__device__ __forceinline__ void stg128(void* p, uint32_t a, uint32_t b, uint32_t c, uint32_t d) {
    asm volatile("st.global.v4.b32 [%0], {%1, %2, %3, %4};" ::"l"(p), "r"(a), "r"(b), "r"(c), "r"(d) : "memory");
}

__device__ __forceinline__ unsigned ld_relaxed(const void* p) {
    unsigned v; asm volatile("ld.relaxed.gpu.global.u32 %0, [%1];" : "=r"(v) : "l"(p) : "memory"); return v;
}
__device__ __forceinline__ void read_l2(uint32_t dst, const void* src, uint32_t on) {
    asm volatile("{\n.reg .pred p;\nsetp.ne.u32 p, %2, 0;\n@p cp.async.cg.shared.global [%0], [%1], 16;\n}\ncp.async.commit_group;" ::"r"(dst), "l"(src), "r"(on) : "memory");
}
template <int N> __device__ __forceinline__ void read_wait() { asm volatile("cp.async.wait_group %0;" ::"n"(N) : "memory"); __syncwarp(); }
__device__ __forceinline__ void read_arrive(uint32_t bar) { asm volatile("cp.async.mbarrier.arrive.noinc.shared::cta.b64 [%0];" ::"r"(bar) : "memory"); }
__device__ __forceinline__ unsigned after(unsigned n, unsigned p, unsigned z) {
    unsigned r; asm volatile("lop3.b32 %0, %1, %2, %3, 0xea;" : "=r"(r) : "r"(p), "r"(z), "r"(n)); return r;
}
__device__ __forceinline__ void red_add(unsigned* f, unsigned n) { asm volatile("red.relaxed.gpu.global.add.u32 [%0], %1;" ::"l"(f), "r"(n) : "memory"); }
__device__ __forceinline__ void poll_ge(const unsigned* f, unsigned v, unsigned ready) {
    asm volatile(
        "{\n.reg .pred p;\n.reg .b32 v, n;\n"
        "setp.lt.u32 p, %1, %2;\n"
        "vote.sync.any.pred p, p, 0xffffffff;\n"
        "@!p bra.uni LAB_DONE;\n"
        "mov.b32 n, 0;\n"
        "LAB_POLL:\n"
        "ld.relaxed.gpu.global.u32 v, [%0];\n"
        "setp.lt.u32 p, v, %2;\n"
        "vote.sync.any.pred p, p, 0xffffffff;\n"
        "@!p bra.uni LAB_DONE;\n"
        "add.u32 n, n, 1;\n"
        "setp.lt.u32 p, n, 0x400000;\n"
        "@p bra.uni LAB_POLL;\n"
        "LAB_DONE:\n}\n" ::"l"(f), "r"(v), "r"(ready) : "memory");
}

__device__ __forceinline__ uint32_t pack_bf16(float lo, float hi) {
    uint32_t r; asm("cvt.rn.bf16x2.f32 %0, %1, %2;" : "=r"(r) : "f"(hi), "f"(lo)); return r;
}
__device__ __forceinline__ uint32_t mul_bf16x2(uint32_t a, uint32_t b) { uint32_t r; asm("mul.rn.bf16x2 %0, %1, %2;" : "=r"(r) : "r"(a), "r"(b)); return r; }
__device__ __forceinline__ uint32_t prmt(uint32_t a, uint32_t b, uint32_t s) { uint32_t r; asm("prmt.b32 %0, %1, %2, %3;" : "=r"(r) : "r"(a), "r"(b), "r"(s)); return r; }
__device__ __forceinline__ uint32_t madi(uint32_t hi, uint32_t m, uint32_t lo) { uint32_t r; asm("mad.lo.u32 %0, %1, %2, %3;" : "=r"(r) : "r"(hi), "r"(m), "r"(lo)); return r; }
__device__ __forceinline__ uint32_t pack8(const uint4& a, const uint4& b) {
    return madi(madi(madi(b.w, 65536, a.w), 16, madi(b.z, 65536, a.z)), 256, madi(madi(b.y, 65536, a.y), 16, madi(b.x, 65536, a.x)));
}
struct Lut { uint32_t lo[4], hi[4]; };
__device__ __forceinline__ void lookup4(uint32_t s7, uint32_t sel, const Lut& t, uint32_t& w01, uint32_t& w23) {
    const uint32_t lo = prmt(prmt(t.lo[0], t.lo[1], s7), prmt(t.lo[2], t.lo[3], s7), sel);
    const uint32_t hi = prmt(prmt(t.hi[0], t.hi[1], s7), prmt(t.hi[2], t.hi[3], s7), sel);
    w01 = prmt(lo, hi, 0x5140);
    w23 = prmt(lo, hi, 0x7362);
}
__device__ __forceinline__ uint4 dequant8(uint32_t p, const uint4& sc, const Lut& t) {
    const uint32_t m8 = p & 0x88888888u, s7 = p & 0x77777777u;
    uint4 r;
    lookup4(s7, (m8 >> 1) + 0x3210u, t, r.x, r.y);
    lookup4(s7 >> 16, (m8 >> 17) + 0x3210u, t, r.z, r.w);
    r.x = mul_bf16x2(r.x, sc.x); r.y = mul_bf16x2(r.y, sc.y); r.z = mul_bf16x2(r.z, sc.z); r.w = mul_bf16x2(r.w, sc.w);
    return r;
}
__device__ __forceinline__ uint4 dequant8_shfl(const uint4& q0, const uint4& q1, const uint4& sc, uint32_t tab) {
    uint4 r;
    r.x = mul_bf16x2(__byte_perm(__shfl_sync(~0u, tab, q0.x), __shfl_sync(~0u, tab, q0.y), 0x5410), sc.x);
    r.y = mul_bf16x2(__byte_perm(__shfl_sync(~0u, tab, q0.z), __shfl_sync(~0u, tab, q0.w), 0x5410), sc.y);
    r.z = mul_bf16x2(__byte_perm(__shfl_sync(~0u, tab, q1.x), __shfl_sync(~0u, tab, q1.y), 0x5410), sc.z);
    r.w = mul_bf16x2(__byte_perm(__shfl_sync(~0u, tab, q1.z), __shfl_sync(~0u, tab, q1.w), 0x5410), sc.w);
    return r;
}

__device__ __forceinline__ void wgmma_fence() { asm volatile("wgmma.fence.sync.aligned;" ::: "memory"); }
__device__ __forceinline__ void wgmma_commit() { asm volatile("wgmma.commit_group.sync.aligned;" ::: "memory"); }
template <int N> __device__ __forceinline__ void wgmma_wait() { asm volatile("wgmma.wait_group.sync.aligned %0;" ::"n"(N) : "memory"); }
template <int SCALE_D>
__device__ __forceinline__ void wgmma_ss(float (&d)[112], uint32_t descA, uint32_t descB) {
    asm volatile(
        "{\n.reg .pred p;\n.reg .b64 da, db;\nsetp.ne.b32 p, %114, 0;\n"
        "mov.b64 da, {%112, 0x40000040};\nmov.b64 db, {%113, 0x10};\n"
        "wgmma.mma_async.sync.aligned.m64n224k16.f32.bf16.bf16 "
        "{%0, %1, %2, %3, %4, %5, %6, %7, %8, %9, %10, %11, %12, %13, %14, %15, "
        "%16, %17, %18, %19, %20, %21, %22, %23, %24, %25, %26, %27, %28, %29, %30, %31, "
        "%32, %33, %34, %35, %36, %37, %38, %39, %40, %41, %42, %43, %44, %45, %46, %47, "
        "%48, %49, %50, %51, %52, %53, %54, %55, %56, %57, %58, %59, %60, %61, %62, %63, "
        "%64, %65, %66, %67, %68, %69, %70, %71, %72, %73, %74, %75, %76, %77, %78, %79, "
        "%80, %81, %82, %83, %84, %85, %86, %87, %88, %89, %90, %91, %92, %93, %94, %95, "
        "%96, %97, %98, %99, %100, %101, %102, %103, %104, %105, %106, %107, %108, %109, %110, %111}, "
        "da, db, p, 1, 1, 0, 1;\n}\n"
        : "+f"(d[0]), "+f"(d[1]), "+f"(d[2]), "+f"(d[3]), "+f"(d[4]), "+f"(d[5]), "+f"(d[6]), "+f"(d[7]),
          "+f"(d[8]), "+f"(d[9]), "+f"(d[10]), "+f"(d[11]), "+f"(d[12]), "+f"(d[13]), "+f"(d[14]), "+f"(d[15]),
          "+f"(d[16]), "+f"(d[17]), "+f"(d[18]), "+f"(d[19]), "+f"(d[20]), "+f"(d[21]), "+f"(d[22]), "+f"(d[23]),
          "+f"(d[24]), "+f"(d[25]), "+f"(d[26]), "+f"(d[27]), "+f"(d[28]), "+f"(d[29]), "+f"(d[30]), "+f"(d[31]),
          "+f"(d[32]), "+f"(d[33]), "+f"(d[34]), "+f"(d[35]), "+f"(d[36]), "+f"(d[37]), "+f"(d[38]), "+f"(d[39]),
          "+f"(d[40]), "+f"(d[41]), "+f"(d[42]), "+f"(d[43]), "+f"(d[44]), "+f"(d[45]), "+f"(d[46]), "+f"(d[47]),
          "+f"(d[48]), "+f"(d[49]), "+f"(d[50]), "+f"(d[51]), "+f"(d[52]), "+f"(d[53]), "+f"(d[54]), "+f"(d[55]),
          "+f"(d[56]), "+f"(d[57]), "+f"(d[58]), "+f"(d[59]), "+f"(d[60]), "+f"(d[61]), "+f"(d[62]), "+f"(d[63]),
          "+f"(d[64]), "+f"(d[65]), "+f"(d[66]), "+f"(d[67]), "+f"(d[68]), "+f"(d[69]), "+f"(d[70]), "+f"(d[71]),
          "+f"(d[72]), "+f"(d[73]), "+f"(d[74]), "+f"(d[75]), "+f"(d[76]), "+f"(d[77]), "+f"(d[78]), "+f"(d[79]),
          "+f"(d[80]), "+f"(d[81]), "+f"(d[82]), "+f"(d[83]), "+f"(d[84]), "+f"(d[85]), "+f"(d[86]), "+f"(d[87]),
          "+f"(d[88]), "+f"(d[89]), "+f"(d[90]), "+f"(d[91]), "+f"(d[92]), "+f"(d[93]), "+f"(d[94]), "+f"(d[95]),
          "+f"(d[96]), "+f"(d[97]), "+f"(d[98]), "+f"(d[99]), "+f"(d[100]), "+f"(d[101]), "+f"(d[102]), "+f"(d[103]),
          "+f"(d[104]), "+f"(d[105]), "+f"(d[106]), "+f"(d[107]), "+f"(d[108]), "+f"(d[109]), "+f"(d[110]), "+f"(d[111])
        : "r"(descA), "r"(descB), "n"(SCALE_D));
}

template <int SCALE_D>
__device__ __forceinline__ void wgmma_ss(float (&d)[64], uint32_t descA, uint32_t descB) {
    asm volatile(
        "{\n.reg .pred p;\n.reg .b64 da, db;\nsetp.ne.b32 p, %66, 0;\n"
        "mov.b64 da, {%64, 0x40000040};\nmov.b64 db, {%65, 0x10};\n"
        "wgmma.mma_async.sync.aligned.m64n128k16.f32.bf16.bf16 "
        "{%0, %1, %2, %3, %4, %5, %6, %7, %8, %9, %10, %11, %12, %13, %14, %15, "
        "%16, %17, %18, %19, %20, %21, %22, %23, %24, %25, %26, %27, %28, %29, %30, %31, "
        "%32, %33, %34, %35, %36, %37, %38, %39, %40, %41, %42, %43, %44, %45, %46, %47, "
        "%48, %49, %50, %51, %52, %53, %54, %55, %56, %57, %58, %59, %60, %61, %62, %63}, "
        "da, db, p, 1, 1, 0, 1;\n}\n"
        : "+f"(d[0]), "+f"(d[1]), "+f"(d[2]), "+f"(d[3]), "+f"(d[4]), "+f"(d[5]), "+f"(d[6]), "+f"(d[7]),
          "+f"(d[8]), "+f"(d[9]), "+f"(d[10]), "+f"(d[11]), "+f"(d[12]), "+f"(d[13]), "+f"(d[14]), "+f"(d[15]),
          "+f"(d[16]), "+f"(d[17]), "+f"(d[18]), "+f"(d[19]), "+f"(d[20]), "+f"(d[21]), "+f"(d[22]), "+f"(d[23]),
          "+f"(d[24]), "+f"(d[25]), "+f"(d[26]), "+f"(d[27]), "+f"(d[28]), "+f"(d[29]), "+f"(d[30]), "+f"(d[31]),
          "+f"(d[32]), "+f"(d[33]), "+f"(d[34]), "+f"(d[35]), "+f"(d[36]), "+f"(d[37]), "+f"(d[38]), "+f"(d[39]),
          "+f"(d[40]), "+f"(d[41]), "+f"(d[42]), "+f"(d[43]), "+f"(d[44]), "+f"(d[45]), "+f"(d[46]), "+f"(d[47]),
          "+f"(d[48]), "+f"(d[49]), "+f"(d[50]), "+f"(d[51]), "+f"(d[52]), "+f"(d[53]), "+f"(d[54]), "+f"(d[55]),
          "+f"(d[56]), "+f"(d[57]), "+f"(d[58]), "+f"(d[59]), "+f"(d[60]), "+f"(d[61]), "+f"(d[62]), "+f"(d[63])
        : "r"(descA), "r"(descB), "n"(SCALE_D));
}

template <int SCALE_D>
__device__ __forceinline__ void wgmma_ss(float (&d)[32], uint32_t descA, uint32_t descB) {
    asm volatile(
        "{\n.reg .pred p;\n.reg .b64 da, db;\nsetp.ne.b32 p, %34, 0;\n"
        "mov.b64 da, {%32, 0x40000040};\nmov.b64 db, {%33, 0x10};\n"
        "wgmma.mma_async.sync.aligned.m64n64k16.f32.bf16.bf16 "
        "{%0, %1, %2, %3, %4, %5, %6, %7, %8, %9, %10, %11, %12, %13, %14, %15, "
        "%16, %17, %18, %19, %20, %21, %22, %23, %24, %25, %26, %27, %28, %29, %30, %31}, "
        "da, db, p, 1, 1, 0, 1;\n}\n"
        : "+f"(d[0]), "+f"(d[1]), "+f"(d[2]), "+f"(d[3]), "+f"(d[4]), "+f"(d[5]), "+f"(d[6]), "+f"(d[7]),
          "+f"(d[8]), "+f"(d[9]), "+f"(d[10]), "+f"(d[11]), "+f"(d[12]), "+f"(d[13]), "+f"(d[14]), "+f"(d[15]),
          "+f"(d[16]), "+f"(d[17]), "+f"(d[18]), "+f"(d[19]), "+f"(d[20]), "+f"(d[21]), "+f"(d[22]), "+f"(d[23]),
          "+f"(d[24]), "+f"(d[25]), "+f"(d[26]), "+f"(d[27]), "+f"(d[28]), "+f"(d[29]), "+f"(d[30]), "+f"(d[31])
        : "r"(descA), "r"(descB), "n"(SCALE_D));
}

template <int SCALE_D>
__device__ __forceinline__ void wgmma_ss(float (&d)[16], uint32_t descA, uint32_t descB) {
    asm volatile(
        "{\n.reg .pred p;\n.reg .b64 da, db;\nsetp.ne.b32 p, %18, 0;\n"
        "mov.b64 da, {%16, 0x40000040};\nmov.b64 db, {%17, 0x10};\n"
        "wgmma.mma_async.sync.aligned.m64n32k16.f32.bf16.bf16 "
        "{%0, %1, %2, %3, %4, %5, %6, %7, %8, %9, %10, %11, %12, %13, %14, %15}, "
        "da, db, p, 1, 1, 0, 1;\n}\n"
        : "+f"(d[0]), "+f"(d[1]), "+f"(d[2]), "+f"(d[3]), "+f"(d[4]), "+f"(d[5]), "+f"(d[6]), "+f"(d[7]),
          "+f"(d[8]), "+f"(d[9]), "+f"(d[10]), "+f"(d[11]), "+f"(d[12]), "+f"(d[13]), "+f"(d[14]), "+f"(d[15])
        : "r"(descA), "r"(descB), "n"(SCALE_D));
}

__device__ __forceinline__ void wgmma_rs(float (&d)[64], const uint4& a, uint32_t descB) {
    asm volatile(
        "{\n.reg .pred p;\n.reg .b64 db;\nsetp.eq.b32 p, 0, 0;\n"
        "mov.b64 db, {%68, 0x10};\n"
        "wgmma.mma_async.sync.aligned.m64n128k16.f32.bf16.bf16 "
        "{%0, %1, %2, %3, %4, %5, %6, %7, %8, %9, %10, %11, %12, %13, %14, %15, "
        "%16, %17, %18, %19, %20, %21, %22, %23, %24, %25, %26, %27, %28, %29, %30, %31, "
        "%32, %33, %34, %35, %36, %37, %38, %39, %40, %41, %42, %43, %44, %45, %46, %47, "
        "%48, %49, %50, %51, %52, %53, %54, %55, %56, %57, %58, %59, %60, %61, %62, %63}, "
        "{%64, %65, %66, %67}, db, p, 1, 1, 1;\n}\n"
        : "+f"(d[0]), "+f"(d[1]), "+f"(d[2]), "+f"(d[3]), "+f"(d[4]), "+f"(d[5]), "+f"(d[6]), "+f"(d[7]),
          "+f"(d[8]), "+f"(d[9]), "+f"(d[10]), "+f"(d[11]), "+f"(d[12]), "+f"(d[13]), "+f"(d[14]), "+f"(d[15]),
          "+f"(d[16]), "+f"(d[17]), "+f"(d[18]), "+f"(d[19]), "+f"(d[20]), "+f"(d[21]), "+f"(d[22]), "+f"(d[23]),
          "+f"(d[24]), "+f"(d[25]), "+f"(d[26]), "+f"(d[27]), "+f"(d[28]), "+f"(d[29]), "+f"(d[30]), "+f"(d[31]),
          "+f"(d[32]), "+f"(d[33]), "+f"(d[34]), "+f"(d[35]), "+f"(d[36]), "+f"(d[37]), "+f"(d[38]), "+f"(d[39]),
          "+f"(d[40]), "+f"(d[41]), "+f"(d[42]), "+f"(d[43]), "+f"(d[44]), "+f"(d[45]), "+f"(d[46]), "+f"(d[47]),
          "+f"(d[48]), "+f"(d[49]), "+f"(d[50]), "+f"(d[51]), "+f"(d[52]), "+f"(d[53]), "+f"(d[54]), "+f"(d[55]),
          "+f"(d[56]), "+f"(d[57]), "+f"(d[58]), "+f"(d[59]), "+f"(d[60]), "+f"(d[61]), "+f"(d[62]), "+f"(d[63])
        : "r"(a.x), "r"(a.y), "r"(a.z), "r"(a.w), "r"(descB));
}

__device__ __forceinline__ void wgmma_rs(float (&d)[32], const uint4& a, uint32_t descB) {
    asm volatile(
        "{\n.reg .pred p;\n.reg .b64 db;\nsetp.eq.b32 p, 0, 0;\n"
        "mov.b64 db, {%36, 0x10};\n"
        "wgmma.mma_async.sync.aligned.m64n64k16.f32.bf16.bf16 "
        "{%0, %1, %2, %3, %4, %5, %6, %7, %8, %9, %10, %11, %12, %13, %14, %15, "
        "%16, %17, %18, %19, %20, %21, %22, %23, %24, %25, %26, %27, %28, %29, %30, %31}, "
        "{%32, %33, %34, %35}, db, p, 1, 1, 1;\n}\n"
        : "+f"(d[0]), "+f"(d[1]), "+f"(d[2]), "+f"(d[3]), "+f"(d[4]), "+f"(d[5]), "+f"(d[6]), "+f"(d[7]),
          "+f"(d[8]), "+f"(d[9]), "+f"(d[10]), "+f"(d[11]), "+f"(d[12]), "+f"(d[13]), "+f"(d[14]), "+f"(d[15]),
          "+f"(d[16]), "+f"(d[17]), "+f"(d[18]), "+f"(d[19]), "+f"(d[20]), "+f"(d[21]), "+f"(d[22]), "+f"(d[23]),
          "+f"(d[24]), "+f"(d[25]), "+f"(d[26]), "+f"(d[27]), "+f"(d[28]), "+f"(d[29]), "+f"(d[30]), "+f"(d[31])
        : "r"(a.x), "r"(a.y), "r"(a.z), "r"(a.w), "r"(descB));
}

__device__ __forceinline__ void wgmma_rs(float (&d)[16], const uint4& a, uint32_t descB) {
    asm volatile(
        "{\n.reg .pred p;\n.reg .b64 db;\nsetp.eq.b32 p, 0, 0;\n"
        "mov.b64 db, {%20, 0x10};\n"
        "wgmma.mma_async.sync.aligned.m64n32k16.f32.bf16.bf16 "
        "{%0, %1, %2, %3, %4, %5, %6, %7, %8, %9, %10, %11, %12, %13, %14, %15}, "
        "{%16, %17, %18, %19}, db, p, 1, 1, 1;\n}\n"
        : "+f"(d[0]), "+f"(d[1]), "+f"(d[2]), "+f"(d[3]), "+f"(d[4]), "+f"(d[5]), "+f"(d[6]), "+f"(d[7]),
          "+f"(d[8]), "+f"(d[9]), "+f"(d[10]), "+f"(d[11]), "+f"(d[12]), "+f"(d[13]), "+f"(d[14]), "+f"(d[15])
        : "r"(a.x), "r"(a.y), "r"(a.z), "r"(a.w), "r"(descB));
}

constexpr int NT = N_ / BN, MT = M_ / BM;
constexpr int W_BYTES = BN * BK * 2;
constexpr int SLAB = 8 * BN * 4;
constexpr int SC_ROW = BN * 2;
constexpr int X_OFF = 0;
constexpr int W_OFF = 10 * 8192;
constexpr int R_OFF = W_OFF + 4 * W_BYTES;
constexpr int SC_OFF = R_OFF + W_BYTES - 2 * SC_ROW;
constexpr int RAW0_OFF = W_OFF + 2 * W_BYTES;
constexpr int SC0_OFF = W_OFF + 3 * W_BYTES;
constexpr int BAR_OFF = SC_OFF + 16 * SC_ROW;
constexpr int SMEM_BYTES = BAR_OFF + 896;
constexpr unsigned READY = MT * 7;
constexpr int UM = 22;
constexpr int NAG = 7;

__device__ __align__(1024) uint8_t g_wimg[(size_t)NT * KC * W_BYTES];
__device__ unsigned g_flag[NT * 32];

__host__ __device__ constexpr int slab_at(int u) { return u == 0 ? 2 : u == 1 ? 3 : u == 3 ? 4 : u == 5 ? 5 : (u >= 7 && u <= 16) ? u - 1 : -1; }
__host__ __device__ constexpr int wload_at(int u) {
    return u <= 10 ? ((u & 1) ? -1 : u / 2 + 1) : u <= 17 ? ((u & 1) ? (u + 3) / 2 : -1) : u == 18 ? 11 : u == 19 ? 12 : u == 20 ? 15 : u == 21 ? 13 : -1;
}
__host__ __device__ constexpr int tail_chunk(int j) { return j == 3 ? 15 : j == 4 ? 14 : 11 + j; }
__host__ __device__ constexpr int wbuf(int c) { return c == 15 ? 4 : c & 3; }

template <int NR>
__device__ __forceinline__ void store_cols(const float (&acc)[NR], int j0, int j1, uint8_t* p) {
#pragma unroll
    for (int j = j0; j < j1; j++) {
        const int i = 16 * j;
        stg128(p + j * 64, pack_bf16(acc[i], acc[i + 1]), pack_bf16(acc[i + 4], acc[i + 5]), pack_bf16(acc[i + 8], acc[i + 9]), pack_bf16(acc[i + 12], acc[i + 13]));
        stg128(p + j * 64 + 8 * N_ * 2, pack_bf16(acc[i + 2], acc[i + 3]), pack_bf16(acc[i + 6], acc[i + 7]), pack_bf16(acc[i + 10], acc[i + 11]), pack_bf16(acc[i + 14], acc[i + 15]));
    }
}

__global__ void __cluster_dims__(2, 1, 1) __launch_bounds__(256, 1)
nf4_gemm_kernel(const uint8_t* __restrict__ qw, const __nv_bfloat16* __restrict__ cb, const __nv_bfloat16* __restrict__ absmax,
                uint8_t* __restrict__ wimg, unsigned* __restrict__ gflags, uint8_t* __restrict__ out, const unsigned zero,
                const __grid_constant__ CUtensorMap tmx, const __grid_constant__ CUtensorMap tmx64, const __grid_constant__ CUtensorMap tmq16,
                const __grid_constant__ CUtensorMap tmq8, const __grid_constant__ CUtensorMap tmq1, const __grid_constant__ CUtensorMap tms) {
    extern __shared__ __align__(1024) uint8_t smem[];
    const int rank = blockIdx.x & 1;
    const int mt = (blockIdx.x >> 5) * 2 + rank, nt = (blockIdx.x >> 1) & 15;
    const uint8_t* share;
    asm volatile(
        "{\n.reg .b32 t, b, o, h;\n.reg .b64 a;\n"
        "mov.u32 t, %%tid.x;\nmov.u32 b, %%ctaid.x;\n"
        "shr.u32 h, t, 5;\nshl.b32 o, t, 5;\nmad.lo.u32 o, h, %2 - 1024, o;\n"
        "and.b32 h, b, 1;\nmad.lo.u32 o, h, 8 * %2 - %3 / 2, o;\n"
        "shr.u32 h, b, 5;\nmad.lo.u32 o, h, 16 * %2 - 16 * %3, o;\n"
        "mad.lo.u32 o, b, %3 / 2, o;\n"
        "cvt.u64.u32 a, o;\nadd.u64 a, a, %1;\n"
        "prefetch.global.L2 [a + 64 * %2];\n"
        "mov.b64 %0, a;\n}\n" : "=l"(share) : "l"(qw), "n"(N_ * 4), "n"(BN * 4));
    const uint32_t sbase = smem_u32(smem);
    const int warp = __shfl_sync(~0u, (int)(threadIdx.x >> 5), 0);
    const int wg = warp >> 2, wj = warp & 3;
    const int lane = threadIdx.x & 31;
    const uint32_t bars = sbase + BAR_OFF;
    const uint32_t snap = bars;
    const uint32_t xfull = bars + 64 + wg * 40;
    const uint32_t wfull = bars + 144;
    const uint32_t wempty = bars + 184;
    const uint32_t ringfull = bars + 216;
    const uint32_t rawbar = bars + 248;
    const uint32_t wown = bars + 264;
    const uint32_t stored = bars + 272 - 8;
    const uint32_t wlast = bars + 344;
    const uint32_t xbase = sbase + X_OFF + wg * 40960, wbase = sbase + W_OFF, rbase = sbase + R_OFF;
    const int xrow = mt * BM + wg * 128 + wj * 16;
    const uint8_t* wsrc = wimg + (size_t)nt * KC * W_BYTES;
    unsigned* flags = gflags + nt * 32;

    auto load_x = [&](int u, int cs = -1) {
        const int c = u < UM ? u >> 1 : tail_chunk((u - UM) % 5), b = u < UM ? u & 1 : (u - UM) / 5;
        mbar_expect_tx(xfull + 8 * (u % 5), cs >= 0 ? 3072 : 2048);
        tma_load_2d(xbase + (u % 5) * 8192 + wj * 2048, &tmx, c * BK, xrow + b * 64, xfull + 8 * (u % 5));
        if (cs >= 0) tma_load_2d(rbase + (cs & 3) * SLAB + warp * 1024, &tmq1, nt * BN + warp * 32, cs * BK + mt * 8, xfull + 8 * (u % 5));
    };
    auto load_x64 = [&](int g, int u) {
        const uint32_t bar = bars + 64 + g * 40 + 8 * u;
        mbar_arrive_n(bar, 3);
        mbar_expect_tx(bar, 8192);
        tma_load_2d(sbase + X_OFF + g * 40960 + u * 8192, &tmx64, (u >> 1) * BK, mt * BM + g * 128 + (u & 1) * 64, bar);
    };
    auto load_slab = [&](int c, uint32_t extra = 0) {
        mbar_expect_tx(ringfull + 8 * (c & 3), SLAB + extra);
        tma_load_3d(rbase + (c & 3) * SLAB, &tmq8, 0, c * BK + mt * 8, nt * 7, ringfull + 8 * (c & 3));
    };
    auto load_raw = [&](int p, uint32_t extra = 0) {
        mbar_expect_tx(rawbar + 8 * p, 2 * SLAB + extra);
        tma_load_3d(sbase + RAW0_OFF + p * 2 * SLAB, &tmq16, 0, rank * 32 + p * 16, nt * 7, rawbar + 8 * p);
    };
    if (warp == 7) {
        if (elect()) {
            mbar_init(ringfull + 8, 1); mbar_init(rawbar, 1); mbar_init(rawbar + 8, 1);
            load_slab(1, SC_ROW);
            bulk_load(sbase + SC0_OFF + SC_ROW, absmax + N_ + nt * BN, SC_ROW, ringfull + 8);
            load_raw(0, SC_ROW);
            bulk_load(sbase + SC0_OFF, absmax + nt * BN, SC_ROW, rawbar);
            load_raw(1);
            mbar_init(bars + 64, 4); mbar_init(bars + 72, 4); mbar_init(bars + 104, 4); mbar_init(bars + 112, 4); mbar_init(ringfull + 16, 1);
            mbar_init_fence();
        }
        __syncwarp();
    }
    uint4 c0, c1;
    asm volatile("ld.global.nc.v4.u32 {%0, %1, %2, %3}, [%8];\nld.global.nc.v4.u32 {%4, %5, %6, %7}, [%8 + 16];"
                 : "=r"(c0.x), "=r"(c0.y), "=r"(c0.z), "=r"(c0.w), "=r"(c1.x), "=r"(c1.y), "=r"(c1.z), "=r"(c1.w) : "l"(cb));
    if (warp < 7) delay(200);
    asm volatile("prefetch.global.L2 [%0];" ::"l"(share));
    if (warp == 5 || warp == 6) {
        if (elect()) {
            if (warp == 6) {
#pragma unroll
                for (int s = 0; s < 5; s++) mbar_init(wfull + 8 * s, 1);
#pragma unroll
                for (int s = 0; s < 4; s++) mbar_init(wempty + 8 * s, 16);
                mbar_init(wown, 7); mbar_init(wlast, 1); mbar_init(ringfull, 1); mbar_init(ringfull + 24, 1);
                mbar_expect_tx(wfull, W_BYTES / 2);
            }
            if (warp == 5) {
#pragma unroll
                for (int s = 0; s < 10; s++) if (s % 5 >= 2) mbar_init(bars + 64 + 8 * s, 4);
#pragma unroll
                for (int s = 1; s <= NAG; s++) mbar_init(stored + 8 * s, s == 1 ? 7 : 224);
            }
            mbar_init_fence();
        }
        __syncwarp();
    }
    cluster_arrive();
    if (warp == 7) {
        if (elect()) { load_x64(0, 0); load_x64(0, 1); load_x64(1, 0); load_x64(1, 1); }
        __syncwarp();
    }
    const uint32_t rlane = (lane & 7) * 128 + ((((lane >> 3) * 2) ^ (lane & 7)) << 4);
    const uint32_t wlane = warp * 1024 + (lane & 7) * 16 + (lane >> 3) * 4;
    const uint32_t slabsrc = __shfl_sync(~0u, (warp < 7 ? warp * 1024 + rlane : 0) + sbase, lane);
    const uint32_t scsrc = __shfl_sync(~0u, sbase + (warp < 7 ? warp * 64 : 0) + (lane >> 3) * 16, lane);
    uint8_t* const gdst = wimg + (size_t)nt * KC * W_BYTES + (mt >> 1) * SLAB + (mt & 1) * 128 + wlane;
    uint8_t* const gkeep = (uint8_t*)__shfl_sync(~0u, (unsigned long long)gdst, lane);
    uint8_t* const gread = (uint8_t*)__shfl_sync(~0u, (unsigned long long)(warp < 7 ? gdst + (lane >> 3) * 252 : (uint8_t*)flags + (lane >> 3) * 16), lane);
    Lut lut = {};
    if (warp < 7) {
        lut.lo[0] = __byte_perm(c0.x, c0.y, 0x6420); lut.hi[0] = __byte_perm(c0.x, c0.y, 0x7531);
        lut.lo[1] = __byte_perm(c0.z, c0.w, 0x6420); lut.hi[1] = __byte_perm(c0.z, c0.w, 0x7531);
        lut.lo[2] = __byte_perm(c1.x, c1.y, 0x6420); lut.hi[2] = __byte_perm(c1.x, c1.y, 0x7531);
        lut.lo[3] = __byte_perm(c1.z, c1.w, 0x6420); lut.hi[3] = __byte_perm(c1.z, c1.w, 0x7531);
    }
    cluster_wait();

    auto store_slab = [&](int c, uint32_t p, const uint4& sc) {
        const uint4 w = dequant8(p, sc, lut);
        uint8_t* g = gkeep + (size_t)c * W_BYTES;
        stg32(g, w.x); stg32(g + 256, w.y); stg32(g + 512, w.z); stg32(g + 768, w.w);
        if (c == 1) {
            __syncwarp();
            if (elect()) mbar_arrive(stored + 8);
            __syncwarp();
        } else {
            read_l2(scsrc + SC_OFF + SC_ROW * c, gread + (size_t)c * W_BYTES, (lane & 7) == 0);
            if (c <= NAG) read_arrive(stored + 8 * c);
        }
    };
    auto take_sample = [&]() { read_l2(scsrc + BAR_OFF, gread, (lane & 7) == 0); };
    auto load_w = [&](int c) {
        read_wait<0>();
        poll_ge(flags + c, lds32(snap + 4 * c), READY);
        asm volatile("fence.acquire.gpu;" ::: "memory");
        asm volatile("fence.proxy.async.global;" ::: "memory");
        if (c >= 4 && c < 15) mbar_wait(wempty + 8 * (c & 3), ((c >> 2) - 1) & 1);
        if (elect()) {
            if (c == 1) {
                mbar_expect_tx(wfull + 8, W_BYTES / 2);
                bulk_load_mc(wbase + W_BYTES + rank * SLAB, wsrc + W_BYTES + rank * SLAB, SLAB, wfull + 8);
                mbar_expect_tx(wlast, W_BYTES / 2);
                bulk_load_mc(wbase + W_BYTES + (2 + rank) * SLAB, wsrc + W_BYTES + (2 + rank) * SLAB, SLAB, wlast);
            } else {
                mbar_expect_tx(wfull + 8 * wbuf(c), W_BYTES);
                bulk_load_mc(wbase + wbuf(c) * W_BYTES + rank * (W_BYTES / 2), wsrc + (size_t)c * W_BYTES + rank * (W_BYTES / 2), W_BYTES / 2, wfull + 8 * wbuf(c));
            }
        }
        __syncwarp();
    };

    if (warp < 7) {
        mbar_wait(ringfull + 8, 0);
        store_slab(1, pack8(lds128(slabsrc + R_OFF + SLAB), lds128((slabsrc ^ 16) + R_OFF + SLAB)), lds128(scsrc + SC0_OFF + SC_ROW));
        const uint32_t tab = prmt(prmt(lane & 8 ? lut.lo[2] : lut.lo[0], lane & 8 ? lut.lo[3] : lut.lo[1], lane & 7),
                                  prmt(lane & 8 ? lut.hi[2] : lut.hi[0], lane & 8 ? lut.hi[3] : lut.hi[1], lane & 7), 0x40);
        uint4 sc;
#pragma unroll
        for (int p = 0; p < 2; p++) {
            mbar_wait(rawbar + 8 * p, 0);
            if (p == 0) { sc = lds128(scsrc + SC0_OFF); }
            const uint32_t a = sbase + RAW0_OFF + p * 2 * SLAB + warp * 2048;
            const uint4 v0 = lds128(a + rlane), v1 = lds128(a + (rlane ^ 16)), v2 = lds128(a + rlane + 1024), v3 = lds128(a + (rlane ^ 16) + 1024);
            const uint4 w0 = dequant8(pack8(v0, v1), sc, lut), w1 = dequant8_shfl(v2, v3, sc, tab);
            const uint32_t d = wbase + (2 * rank + p) * SLAB, e = d + wlane;
            sts32(e, w0.x); sts32(e + 256, w0.y); sts32(e + 512, w0.z); sts32(e + 768, w0.w);
            sts32(e + 128, w1.x); sts32(e + 384, w1.y); sts32(e + 640, w1.z); sts32(e + 896, w1.w);
            fence_async_smem();
            __syncwarp();
            if (elect()) {
                if (p == 1) mbar_arrive(wown);
                copy_to_peer(d + warp * 1024, 1024, wfull, rank ^ 1);
            }
            __syncwarp();
        }
    } else {
        mbar_wait(stored + 8, 0);
        const unsigned v = ld_relaxed(wsrc + W_BYTES + (mt >> 1) * SLAB + (mt & 1) * 128 + (lane < 28 ? lane : 0) * 256);
        if (elect()) {
            load_slab(2, 14 * SC_ROW);
            tma_load_2d(sbase + SC_OFF + 2 * SC_ROW, &tms, nt * BN, 2, ringfull + 16);
        }
        __syncwarp();
        const unsigned n = after(7, v, zero);
        __syncwarp();
        if (elect()) red_add(flags + 1, n);
        __syncwarp();
        if (elect()) { load_x64(0, 2); load_x64(1, 2); load_x64(0, 3); load_x64(1, 3); load_slab(3); }
        __syncwarp();
    }

    float acc0[112], acc1[112];
    const uint32_t descA = ((xbase & 0x3FFFF) >> 4) | (1u << 16), descB = ((wbase & 0x3FFFF) >> 4) | ((128u >> 4) << 16);
    static_for<0, UM>([&](auto U) __attribute__((always_inline)) {
        constexpr int u = U.value, kc = u >> 1;
        constexpr int c = slab_at(u);
        uint32_t da = descA, db = descB;
        asm volatile("" : "+r"(da), "+r"(db));
        uint4 q0, q1, sc;
        auto slab_loads = [&]() {
            q0 = lds128(slabsrc + R_OFF + (c & 3) * SLAB); q1 = lds128((slabsrc ^ 16) + R_OFF + (c & 3) * SLAB);
            sc = lds128(scsrc + SC_OFF + SC_ROW * c);
        };
        if (u < 4) {
            if (u == 0) mbar_wait3(xfull, 0, xfull + 8, 0, wown, 0);
            if (u == 1) mbar_wait(wfull, 0);
            if (u == 2) mbar_wait3(xfull + 16, 0, xfull + 24, 0, wfull + 8, 0);
            if (u == 3) { mbar_wait2(wlast, 0, ringfull, 0); slab_loads(); }
            if (u == 0 && warp == 7) take_sample();
            const int h = u < 2 ? rank ^ u : u & 1;
            da += kc * 1024 + h * 4; db += kc * (W_BYTES >> 4) + h * (2 * SLAB >> 4);
            wgmma_fence();
            wgmma_ss<u != 0>(acc0, da, db); wgmma_ss<u != 0>(acc1, da + 512, db);
            wgmma_ss<1>(acc0, da + 2, db + (SLAB >> 4)); wgmma_ss<1>(acc1, da + 514, db + (SLAB >> 4));
        } else {
            if (u & 1) mbar_wait(xfull + 8 * (u % 5), (u / 5) & 1);
            else mbar_wait2(xfull + 8 * (u % 5), (u / 5) & 1, wfull + 8 * (kc & 3), (kc >> 2) & 1);
            if (c >= 0) slab_loads();
            da += (u % 5) * 512; db += (kc & 3) * (W_BYTES >> 4);
            wgmma_fence();
#pragma unroll
            for (int ks = 0; ks < 4; ks++) {
                if (u & 1) wgmma_ss<1>(acc1, da + ks * 2, db + ks * (SLAB >> 4));
                else wgmma_ss<1>(acc0, da + ks * 2, db + ks * (SLAB >> 4));
            }
        }
        wgmma_commit();
        if (u >= 2) wgmma_wait<1>();
        if (warp < 7) {
            constexpr int cp = slab_at(u - 2) > NAG ? slab_at(u - 2) : -1;
            if (u < 2) { mbar_wait(ringfull + 8 * c, 0); slab_loads(); }
            uint32_t p = 0;
            if (c >= 0) p = pack8(q0, q1);
            if (cp >= 0) { if (slab_at(u - 1) >= 0) read_wait<1>(); else read_wait<0>(); }
            if (u >= 2) {
                if (elect()) {
                    if (u <= 17) load_x(u + 3, slab_at(u + 3));
                    if (u >= 17) load_x(u + 4);
                    if (!(u & 1)) mbar_arrive_both(wempty + 8 * ((kc - 1) & 3));
                    if (cp >= 0) red_add(flags + cp, 1);
                }
                __syncwarp();
            }
            if (c >= 0) store_slab(c, p, sc);
        } else {
            constexpr int cw = wload_at(u), cc = slab_at(u - 1) <= NAG ? slab_at(u - 1) : -1;
            if (cw >= 0 && cw <= 6) load_w(cw);
            if (u != 1) {
                if (elect()) {
                    if (u == 0) load_slab(4);
                    if (u >= 2 && u <= 17) load_x(u + 3);
                    if (u >= 17) load_x(u + 4);
                    if (u >= 2 && !(u & 1)) mbar_arrive_both(wempty + 8 * ((kc - 1) & 3));
                }
                __syncwarp();
            }
            if (cc >= 0) {
                mbar_wait(stored + 8 * cc, 0);
                if (elect()) red_add(flags + cc, 7);
                __syncwarp();
            }
            if (u == 1) {
                if (elect()) { load_x64(0, 4); load_x64(1, 4); }
                __syncwarp();
                delay(300);
            }
            if (cw > 6) load_w(cw);
            if (wload_at(u + 1) >= 0) take_sample();
        }
    });

    uint32_t tA = descA, tB = descB;
    asm volatile("" : "+r"(tA), "+r"(tB));
    if (wg == 1) {
        wgmma_wait<0>();
        if (elect()) { load_x(UM + 4); mbar_arrive_both(wempty + 16); }
        __syncwarp();
        if (warp == 7) load_w(14);
        if (warp == 7 && lane == 0) {
            if (atomicAdd(flags + 16, 1) == MT - 1) {
#pragma unroll
                for (int c = 0; c <= 16; c++) flags[c] = 0;
            }
        }
        __syncwarp();
        bar_sync<256>(1);
    }
#pragma unroll
    for (int j = 0; j < 5; j++) {
        const int c = tail_chunk(j), v = UM + j;
        mbar_wait2(xfull + 8 * (v % 5), (v / 5) & 1, wfull + 8 * wbuf(c), c == 15 ? 0 : (c >> 2) & 1);
        wgmma_fence();
#pragma unroll
        for (int ks = 0; ks < 4; ks++) wgmma_ss<1>(acc0, tA + (v % 5) * 512 + ks * 2, tB + wbuf(c) * (W_BYTES >> 4) + ks * (SLAB >> 4));
        wgmma_commit();
        if (j == 4) bar_arrive<256>(1 + wg);
        if (j == 0) {
            if (wg == 0) {
                wgmma_wait<1>();
                if (elect()) { load_x(UM + 4); mbar_arrive_both(wempty + 16); }
                __syncwarp();
            }
        } else if (j >= 2) {
            wgmma_wait<2>();
            if (elect()) load_x(v + 3);
            __syncwarp();
        }
    }
    wgmma_wait<1>();
    if (elect()) load_x(UM + 8);
    __syncwarp();
    wgmma_wait<0>();
    if (elect()) load_x(UM + 9);
    __syncwarp();
    uint8_t* optr = out + (size_t)(xrow + (lane >> 2)) * (N_ * 2) + nt * (BN * 2) + (lane & 3) * 16;
    float pa[64], pb[32], pc[16];
#pragma unroll
    for (int i = 0; i < 64; i++) asm volatile("mov.b32 %0, %1;" : "=f"(pa[i]) : "f"(acc1[i]));
#pragma unroll
    for (int i = 0; i < 32; i++) asm volatile("mov.b32 %0, %1;" : "=f"(pb[i]) : "f"(acc1[64 + i]));
#pragma unroll
    for (int i = 0; i < 16; i++) asm volatile("mov.b32 %0, %1;" : "=f"(pc[i]) : "f"(acc1[96 + i]));
    uint4 af[16];
    uint32_t pk[56];
    auto store_pk = [&](int h0, int h1) {
#pragma unroll
        for (int h = h0; h < h1; h++) {
            const int i = 8 * (h >> 1) + (h & 1);
            stg128(optr + (h >> 1) * 64 + (h & 1) * (8 * N_ * 2), pk[i], pk[i + 2], pk[i + 4], pk[i + 6]);
        }
    };
    const uint32_t alane = xbase + wj * 2048 + (lane & 15) * 128 + (((lane >> 4) ^ (lane & 7)) << 4);
    static_for<0, 4>([&](auto J) __attribute__((always_inline)) {
        constexpr int j = J.value, v = UM + 5 + j;
        mbar_wait(xfull + 8 * (v % 5), (v / 5) & 1);
#pragma unroll
        for (int ks = 0; ks < 4; ks++) af[4 * j + ks] = ldmatrix_x4((alane ^ (ks * 32)) + (v % 5) * 8192);
#pragma unroll
        for (int i = 16 * j; i < (j < 3 ? 16 * j + 16 : 56); i++) pk[i] = pack_bf16(acc0[2 * i], acc0[2 * i + 1]);
        store_pk(2 * j, 2 * j + 2);
    });
    if (wg == 0) store_pk(8, 14);
    auto piece = [&](auto& d, int cb) {
        wgmma_fence();
#pragma unroll
        for (int j = 0; j < 5; j++) {
            if (cb == 0 && j == 4) { mbar_wait(xfull + 8 * ((UM + 9) % 5), ((UM + 9) / 5) & 1); wgmma_fence(); }
#pragma unroll
            for (int ks = 0; ks < 4; ks++) {
                const uint32_t db = tB + wbuf(tail_chunk(j)) * (W_BYTES >> 4) + ks * (SLAB >> 4) + cb * 64;
                if (j < 4) wgmma_rs(d, af[(4 * j + ks) & 15], db);
                else wgmma_ss<1>(d, tA + ((UM + 9) % 5) * 512 + ks * 2, db);
            }
        }
        wgmma_commit();
    };
    bar_sync<256>(2 + wg);
    piece(pa, 0);
    bar_arrive<256>(3 + wg);
    if (wg == 1) store_pk(8, 14);
    wgmma_wait<0>();
    optr += 64 * N_ * 2;
    store_cols(pa, 0, 3, optr);
    if (wg == 0) store_cols(pa, 3, 4, optr);
    bar_sync<256>(4 + wg);
    piece(pb, 4);
    bar_arrive<256>(5 + wg);
    if (wg == 1) store_cols(pa, 3, 4, optr);
    wgmma_wait<0>();
    if (wg == 0) store_cols(pb, 0, 2, optr + 4 * 64);
    bar_sync<256>(6 + wg);
    piece(pc, 6);
    if (wg == 0) bar_arrive<256>(7);
    else store_cols(pb, 0, 2, optr + 4 * 64);
    cluster_arrive();
    wgmma_wait<0>();
    store_cols(pc, 0, 1, optr + 6 * 64);
    cluster_wait();
}

typedef CUresult (*EncodeFn)(CUtensorMap*, CUtensorMapDataType, cuuint32_t, void*, const cuuint64_t*, const cuuint64_t*,
                             const cuuint32_t*, const cuuint32_t*, CUtensorMapInterleave, CUtensorMapSwizzle,
                             CUtensorMapL2promotion, CUtensorMapFloatOOBfill);

extern "C" void kernel_launch(void* const* d_in, const int* in_sizes, int n_in, void* d_out, int out_size) {
    static EncodeFn encode = nullptr;
    static void *wimg = nullptr, *gflags = nullptr;
    if (!encode) {
        cudaGetSymbolAddress(&wimg, g_wimg);
        cudaGetSymbolAddress(&gflags, g_flag);
        void* fn = nullptr;
        cudaDriverEntryPointQueryResult qr;
        cudaGetDriverEntryPoint("cuTensorMapEncodeTiled", &fn, cudaEnableDefault, &qr);
        encode = (EncodeFn)fn;
        cudaFuncSetAttribute(nf4_gemm_kernel, cudaFuncAttributeMaxDynamicSharedMemorySize, SMEM_BYTES);
    }
    void *x = d_in[0], *qw = d_in[1], *cb = d_in[2], *absmax = d_in[3];
    auto map = [&](CUtensorMapDataType t, int rank, void* p, const cuuint64_t* dims, const cuuint64_t* strides, const cuuint32_t* box, bool swizzle) {
        CUtensorMap m;
        const cuuint32_t es[3] = {1, 1, 1};
        encode(&m, t, rank, p, dims, strides, box, es, CU_TENSOR_MAP_INTERLEAVE_NONE,
               swizzle ? CU_TENSOR_MAP_SWIZZLE_128B : CU_TENSOR_MAP_SWIZZLE_NONE,
               swizzle ? CU_TENSOR_MAP_L2_PROMOTION_L2_128B : CU_TENSOR_MAP_L2_PROMOTION_NONE, CU_TENSOR_MAP_FLOAT_OOB_FILL_NONE);
        return m;
    };
    const cuuint64_t xd[2] = {K_, M_}, xs[1] = {K_ * 2};
    const cuuint64_t q3d[3] = {32, K_, N_ / 32}, q3s[2] = {N_ * 4, 128};
    const cuuint64_t q2d[2] = {N_, K_}, q2s[1] = {N_ * 4};
    const cuuint64_t sd[2] = {N_, KC}, ss[1] = {N_ * 2};
    const cuuint32_t bx[2] = {BK, 16}, bx64[2] = {BK, 64}, bq16[3] = {32, 16, 7}, bq8[3] = {32, 8, 7}, bq1[2] = {32, 8}, bs[2] = {BN, KC - 2};
    nf4_gemm_kernel<<<128, 256, SMEM_BYTES>>>(
        (const uint8_t*)qw, (const __nv_bfloat16*)cb, (const __nv_bfloat16*)absmax, (uint8_t*)wimg, (unsigned*)gflags, (uint8_t*)d_out, 0u,
        map(CU_TENSOR_MAP_DATA_TYPE_BFLOAT16, 2, x, xd, xs, bx, true), map(CU_TENSOR_MAP_DATA_TYPE_BFLOAT16, 2, x, xd, xs, bx64, true),
        map(CU_TENSOR_MAP_DATA_TYPE_INT32, 3, qw, q3d, q3s, bq16, true), map(CU_TENSOR_MAP_DATA_TYPE_INT32, 3, qw, q3d, q3s, bq8, true),
        map(CU_TENSOR_MAP_DATA_TYPE_INT32, 2, qw, q2d, q2s, bq1, true), map(CU_TENSOR_MAP_DATA_TYPE_BFLOAT16, 2, absmax, sd, ss, bs, false));
}
```

```cpp
#include <cuda_runtime.h>
#include <cuda_bf16.h>
#include <cuda.h>
#include <stdint.h>

constexpr int M_ = 2048, K_ = 1024, N_ = 3584;
constexpr int BM = 256, BN = 224, BK = 64;
constexpr int KC = K_ / BK;

__device__ __forceinline__ uint32_t smem_u32(const void* p) { return (uint32_t)__cvta_generic_to_shared(p); }
__device__ __forceinline__ bool elect() {
    uint32_t ok;
    asm volatile("{\n.reg .pred p;\nelect.sync _|p, 0xffffffff;\nselp.u32 %0, 1, 0, p;\n}\n" : "=r"(ok));
    return ok != 0;
}
template <int I> struct IC { static constexpr int value = I; };
template <int I, int N, class F> __device__ __forceinline__ void static_for(F&& f) {
    if constexpr (I < N) { f(IC<I>{}); static_for<I + 1, N>(f); }
}

__device__ __forceinline__ void mbar_init(uint32_t bar, uint32_t cnt) { asm volatile("mbarrier.init.shared::cta.b64 [%0], %1;" ::"r"(bar), "r"(cnt) : "memory"); }
__device__ __forceinline__ void mbar_init_fence() { asm volatile("fence.mbarrier_init.release.cluster;" ::: "memory"); }
__device__ __forceinline__ void mbar_expect_tx(uint32_t bar, uint32_t bytes) { asm volatile("mbarrier.arrive.expect_tx.shared::cta.b64 _, [%0], %1;" ::"r"(bar), "r"(bytes) : "memory"); }
__device__ __forceinline__ void mbar_arrive(uint32_t bar) { asm volatile("mbarrier.arrive.shared::cta.b64 _, [%0];" ::"r"(bar) : "memory"); }
__device__ __forceinline__ void mbar_arrive_n(uint32_t bar, uint32_t n) { asm volatile("mbarrier.arrive.shared::cta.b64 _, [%0], %1;" ::"r"(bar), "r"(n) : "memory"); }
__device__ __forceinline__ void mbar_arrive_both(uint32_t bar) {
    asm volatile("{\n.reg .b32 ra;\nmapa.shared::cluster.u32 ra, %0, 0;\nmbarrier.arrive.shared::cluster.b64 _, [ra];\n"
                 "mapa.shared::cluster.u32 ra, %0, 1;\nmbarrier.arrive.shared::cluster.b64 _, [ra];\n}\n" ::"r"(bar) : "memory");
}
#define MBAR_TRY(p, b, q) "mbarrier.try_wait.parity.shared::cta.b64 " p ", [" b "], " q ";\n"
#define MBAR_WAIT(TRY) \
    "{\n.reg .pred p0, p1, p2;\n.reg .b32 n;\n" TRY "@p0 bra LAB_DONE;\nmov.b32 n, 0;\nLAB_WAIT:\n" TRY \
    "@p0 bra LAB_DONE;\nadd.u32 n, n, 1;\nsetp.lt.u32 p0, n, 0x40000;\n@p0 bra LAB_WAIT;\ntrap;\nLAB_DONE:\n}\n"
__device__ __forceinline__ void mbar_wait(uint32_t b0, uint32_t q0) {
    asm volatile(MBAR_WAIT(MBAR_TRY("p0", "%0", "%1")) ::"r"(b0), "r"(q0) : "memory");
}
__device__ __forceinline__ void mbar_wait2(uint32_t b0, uint32_t q0, uint32_t b1, uint32_t q1) {
    asm volatile(MBAR_WAIT(MBAR_TRY("p0", "%0", "%1") MBAR_TRY("p1", "%2", "%3") "and.pred p0, p0, p1;\n")
                 ::"r"(b0), "r"(q0), "r"(b1), "r"(q1) : "memory");
}
__device__ __forceinline__ void mbar_wait3(uint32_t b0, uint32_t q0, uint32_t b1, uint32_t q1, uint32_t b2, uint32_t q2) {
    asm volatile(MBAR_WAIT(MBAR_TRY("p0", "%0", "%1") MBAR_TRY("p1", "%2", "%3") MBAR_TRY("p2", "%4", "%5") "and.pred p0, p0, p1;\nand.pred p0, p0, p2;\n")
                 ::"r"(b0), "r"(q0), "r"(b1), "r"(q1), "r"(b2), "r"(q2) : "memory");
}
__device__ __forceinline__ void cluster_arrive() { asm volatile("barrier.cluster.arrive.relaxed.aligned;" ::: "memory"); }
__device__ __forceinline__ void cluster_wait() { asm volatile("barrier.cluster.wait.acquire.aligned;" ::: "memory"); }
template <int NTHR> __device__ __forceinline__ void bar_arrive(int id) { asm volatile("bar.arrive %0, %1;" ::"r"(id), "n"(NTHR) : "memory"); }
template <int NTHR> __device__ __forceinline__ void bar_sync(int id) { asm volatile("bar.sync %0, %1;" ::"r"(id), "n"(NTHR) : "memory"); }
__device__ __forceinline__ void delay(unsigned clks) {
    asm volatile(
        "{\n.reg .pred p;\n.reg .b32 t0, t;\n"
        "mov.u32 t0, %%clock;\n"
        "LAB_DELAY:\n"
        "mov.u32 t, %%clock;\n"
        "sub.u32 t, t, t0;\n"
        "setp.lt.u32 p, t, %0;\n"
        "vote.sync.any.pred p, p, 0xffffffff;\n"
        "@p bra.uni LAB_DELAY;\n}\n" ::"r"(clks) : "memory");
}

__device__ __forceinline__ void tma_load_2d(uint32_t dst, const CUtensorMap* tm, int c0, int c1, uint32_t bar) {
    asm volatile("cp.async.bulk.tensor.2d.shared::cluster.global.mbarrier::complete_tx::bytes [%0], [%1, {%2, %3}], [%4];"
                 ::"r"(dst), "l"(tm), "r"(c0), "r"(c1), "r"(bar) : "memory");
}
__device__ __forceinline__ void tma_load_3d(uint32_t dst, const CUtensorMap* tm, int c0, int c1, int c2, uint32_t bar) {
    asm volatile("cp.async.bulk.tensor.3d.shared::cluster.global.mbarrier::complete_tx::bytes [%0], [%1, {%2, %3, %4}], [%5];"
                 ::"r"(dst), "l"(tm), "r"(c0), "r"(c1), "r"(c2), "r"(bar) : "memory");
}
__device__ __forceinline__ void bulk_load(uint32_t dst, const void* src, uint32_t bytes, uint32_t bar) {
    asm volatile("cp.async.bulk.shared::cluster.global.mbarrier::complete_tx::bytes [%0], [%1], %2, [%3];"
                 ::"r"(dst), "l"(src), "r"(bytes), "r"(bar) : "memory");
}
__device__ __forceinline__ void bulk_load_mc(uint32_t dst, const void* src, uint32_t bytes, uint32_t bar) {
    asm volatile("cp.async.bulk.shared::cluster.global.mbarrier::complete_tx::bytes.multicast::cluster [%0], [%1], %2, [%3], %4;"
                 ::"r"(dst), "l"(src), "r"(bytes), "r"(bar), "h"((uint16_t)3) : "memory");
}
__device__ __forceinline__ uint32_t mapa(uint32_t addr, uint32_t cta) {
    uint32_t r; asm("mapa.shared::cluster.u32 %0, %1, %2;" : "=r"(r) : "r"(addr), "r"(cta)); return r;
}
__device__ __forceinline__ void copy_to_peer(uint32_t addr, uint32_t bytes, uint32_t bar, uint32_t peer) {
    asm volatile("cp.async.bulk.shared::cluster.shared::cta.mbarrier::complete_tx::bytes [%0], [%1], %2, [%3];"
                 ::"r"(mapa(addr, peer)), "r"(addr), "r"(bytes), "r"(mapa(bar, peer)) : "memory");
}
__device__ __forceinline__ void fence_async_smem() { asm volatile("fence.proxy.async.shared::cta;" ::: "memory"); }

__device__ __forceinline__ uint4 lds128(uint32_t a) {
    uint4 v; asm volatile("ld.shared.v4.b32 {%0, %1, %2, %3}, [%4];" : "=r"(v.x), "=r"(v.y), "=r"(v.z), "=r"(v.w) : "r"(a) : "memory"); return v;
}
__device__ __forceinline__ uint32_t lds32(uint32_t a) {
    uint32_t v; asm volatile("ld.shared.b32 %0, [%1];" : "=r"(v) : "r"(a) : "memory"); return v;
}
__device__ __forceinline__ uint4 ldmatrix_x4(uint32_t a) {
    uint4 v;
    asm volatile("ldmatrix.sync.aligned.m8n8.x4.shared.b16 {%0, %1, %2, %3}, [%4];" : "=r"(v.x), "=r"(v.y), "=r"(v.z), "=r"(v.w) : "r"(a) : "memory");
    return v;
}
__device__ __forceinline__ void sts32(uint32_t a, uint32_t v) { asm volatile("st.shared.b32 [%0], %1;" ::"r"(a), "r"(v) : "memory"); }
__device__ __forceinline__ void stg32(void* p, uint32_t v) { asm volatile("st.global.b32 [%0], %1;" ::"l"(p), "r"(v) : "memory"); }
__device__ __forceinline__ void stg128(void* p, uint32_t a, uint32_t b, uint32_t c, uint32_t d) {
    asm volatile("st.global.v4.b32 [%0], {%1, %2, %3, %4};" ::"l"(p), "r"(a), "r"(b), "r"(c), "r"(d) : "memory");
}

__device__ __forceinline__ unsigned ld_relaxed(const void* p) {
    unsigned v; asm volatile("ld.relaxed.gpu.global.u32 %0, [%1];" : "=r"(v) : "l"(p) : "memory"); return v;
}
__device__ __forceinline__ void read_l2(uint32_t dst, const void* src, uint32_t on) {
    asm volatile("{\n.reg .pred p;\nsetp.ne.u32 p, %2, 0;\n@p cp.async.cg.shared.global [%0], [%1], 16;\n}\ncp.async.commit_group;" ::"r"(dst), "l"(src), "r"(on) : "memory");
}
template <int N> __device__ __forceinline__ void read_wait() { asm volatile("cp.async.wait_group %0;" ::"n"(N) : "memory"); __syncwarp(); }
__device__ __forceinline__ void read_arrive(uint32_t bar) { asm volatile("cp.async.mbarrier.arrive.noinc.shared::cta.b64 [%0];" ::"r"(bar) : "memory"); }
__device__ __forceinline__ unsigned after(unsigned n, unsigned p, unsigned z) {
    unsigned r; asm volatile("lop3.b32 %0, %1, %2, %3, 0xea;" : "=r"(r) : "r"(p), "r"(z), "r"(n)); return r;
}
__device__ __forceinline__ void red_add(unsigned* f, unsigned n) { asm volatile("red.relaxed.gpu.global.add.u32 [%0], %1;" ::"l"(f), "r"(n) : "memory"); }
__device__ __forceinline__ void poll_ge(const unsigned* f, unsigned v, unsigned ready) {
    asm volatile(
        "{\n.reg .pred p;\n.reg .b32 v, n;\n"
        "setp.lt.u32 p, %1, %2;\n"
        "vote.sync.any.pred p, p, 0xffffffff;\n"
        "@!p bra.uni LAB_DONE;\n"
        "mov.b32 n, 0;\n"
        "LAB_POLL:\n"
        "ld.relaxed.gpu.global.u32 v, [%0];\n"
        "setp.lt.u32 p, v, %2;\n"
        "vote.sync.any.pred p, p, 0xffffffff;\n"
        "@!p bra.uni LAB_DONE;\n"
        "add.u32 n, n, 1;\n"
        "setp.lt.u32 p, n, 0x400000;\n"
        "@p bra.uni LAB_POLL;\n"
        "LAB_DONE:\n}\n" ::"l"(f), "r"(v), "r"(ready) : "memory");
}

__device__ __forceinline__ uint32_t pack_bf16(float lo, float hi) {
    uint32_t r; asm("cvt.rn.bf16x2.f32 %0, %1, %2;" : "=r"(r) : "f"(hi), "f"(lo)); return r;
}
__device__ __forceinline__ uint32_t mul_bf16x2(uint32_t a, uint32_t b) { uint32_t r; asm("mul.rn.bf16x2 %0, %1, %2;" : "=r"(r) : "r"(a), "r"(b)); return r; }
__device__ __forceinline__ uint32_t prmt(uint32_t a, uint32_t b, uint32_t s) { uint32_t r; asm("prmt.b32 %0, %1, %2, %3;" : "=r"(r) : "r"(a), "r"(b), "r"(s)); return r; }
__device__ __forceinline__ uint32_t madi(uint32_t hi, uint32_t m, uint32_t lo) { uint32_t r; asm("mad.lo.u32 %0, %1, %2, %3;" : "=r"(r) : "r"(hi), "r"(m), "r"(lo)); return r; }
__device__ __forceinline__ uint32_t pack8(const uint4& a, const uint4& b) {
    return madi(madi(madi(b.w, 65536, a.w), 16, madi(b.z, 65536, a.z)), 256, madi(madi(b.y, 65536, a.y), 16, madi(b.x, 65536, a.x)));
}
struct Lut { uint32_t lo[4], hi[4]; };
__device__ __forceinline__ void lookup4(uint32_t s7, uint32_t sel, const Lut& t, uint32_t& w01, uint32_t& w23) {
    const uint32_t lo = prmt(prmt(t.lo[0], t.lo[1], s7), prmt(t.lo[2], t.lo[3], s7), sel);
    const uint32_t hi = prmt(prmt(t.hi[0], t.hi[1], s7), prmt(t.hi[2], t.hi[3], s7), sel);
    w01 = prmt(lo, hi, 0x5140);
    w23 = prmt(lo, hi, 0x7362);
}
__device__ __forceinline__ uint4 dequant8(uint32_t p, const uint4& sc, const Lut& t) {
    const uint32_t m8 = p & 0x88888888u, s7 = p & 0x77777777u;
    uint4 r;
    lookup4(s7, (m8 >> 1) + 0x3210u, t, r.x, r.y);
    lookup4(s7 >> 16, (m8 >> 17) + 0x3210u, t, r.z, r.w);
    r.x = mul_bf16x2(r.x, sc.x); r.y = mul_bf16x2(r.y, sc.y); r.z = mul_bf16x2(r.z, sc.z); r.w = mul_bf16x2(r.w, sc.w);
    return r;
}
__device__ __forceinline__ uint4 dequant8_shfl(const uint4& q0, const uint4& q1, const uint4& sc, uint32_t tab) {
    uint4 r;
    r.x = mul_bf16x2(__byte_perm(__shfl_sync(~0u, tab, q0.x), __shfl_sync(~0u, tab, q0.y), 0x5410), sc.x);
    r.y = mul_bf16x2(__byte_perm(__shfl_sync(~0u, tab, q0.z), __shfl_sync(~0u, tab, q0.w), 0x5410), sc.y);
    r.z = mul_bf16x2(__byte_perm(__shfl_sync(~0u, tab, q1.x), __shfl_sync(~0u, tab, q1.y), 0x5410), sc.z);
    r.w = mul_bf16x2(__byte_perm(__shfl_sync(~0u, tab, q1.z), __shfl_sync(~0u, tab, q1.w), 0x5410), sc.w);
    return r;
}

__device__ __forceinline__ void wgmma_fence() { asm volatile("wgmma.fence.sync.aligned;" ::: "memory"); }
__device__ __forceinline__ void wgmma_commit() { asm volatile("wgmma.commit_group.sync.aligned;" ::: "memory"); }
template <int N> __device__ __forceinline__ void wgmma_wait() { asm volatile("wgmma.wait_group.sync.aligned %0;" ::"n"(N) : "memory"); }
template <int SCALE_D>
__device__ __forceinline__ void wgmma_ss(float (&d)[112], uint32_t descA, uint32_t descB) {
    asm volatile(
        "{\n.reg .pred p;\n.reg .b64 da, db;\nsetp.ne.b32 p, %114, 0;\n"
        "mov.b64 da, {%112, 0x40000040};\nmov.b64 db, {%113, 0x10};\n"
        "wgmma.mma_async.sync.aligned.m64n224k16.f32.bf16.bf16 "
        "{%0, %1, %2, %3, %4, %5, %6, %7, %8, %9, %10, %11, %12, %13, %14, %15, "
        "%16, %17, %18, %19, %20, %21, %22, %23, %24, %25, %26, %27, %28, %29, %30, %31, "
        "%32, %33, %34, %35, %36, %37, %38, %39, %40, %41, %42, %43, %44, %45, %46, %47, "
        "%48, %49, %50, %51, %52, %53, %54, %55, %56, %57, %58, %59, %60, %61, %62, %63, "
        "%64, %65, %66, %67, %68, %69, %70, %71, %72, %73, %74, %75, %76, %77, %78, %79, "
        "%80, %81, %82, %83, %84, %85, %86, %87, %88, %89, %90, %91, %92, %93, %94, %95, "
        "%96, %97, %98, %99, %100, %101, %102, %103, %104, %105, %106, %107, %108, %109, %110, %111}, "
        "da, db, p, 1, 1, 0, 1;\n}\n"
        : "+f"(d[0]), "+f"(d[1]), "+f"(d[2]), "+f"(d[3]), "+f"(d[4]), "+f"(d[5]), "+f"(d[6]), "+f"(d[7]),
          "+f"(d[8]), "+f"(d[9]), "+f"(d[10]), "+f"(d[11]), "+f"(d[12]), "+f"(d[13]), "+f"(d[14]), "+f"(d[15]),
          "+f"(d[16]), "+f"(d[17]), "+f"(d[18]), "+f"(d[19]), "+f"(d[20]), "+f"(d[21]), "+f"(d[22]), "+f"(d[23]),
          "+f"(d[24]), "+f"(d[25]), "+f"(d[26]), "+f"(d[27]), "+f"(d[28]), "+f"(d[29]), "+f"(d[30]), "+f"(d[31]),
          "+f"(d[32]), "+f"(d[33]), "+f"(d[34]), "+f"(d[35]), "+f"(d[36]), "+f"(d[37]), "+f"(d[38]), "+f"(d[39]),
          "+f"(d[40]), "+f"(d[41]), "+f"(d[42]), "+f"(d[43]), "+f"(d[44]), "+f"(d[45]), "+f"(d[46]), "+f"(d[47]),
          "+f"(d[48]), "+f"(d[49]), "+f"(d[50]), "+f"(d[51]), "+f"(d[52]), "+f"(d[53]), "+f"(d[54]), "+f"(d[55]),
          "+f"(d[56]), "+f"(d[57]), "+f"(d[58]), "+f"(d[59]), "+f"(d[60]), "+f"(d[61]), "+f"(d[62]), "+f"(d[63]),
          "+f"(d[64]), "+f"(d[65]), "+f"(d[66]), "+f"(d[67]), "+f"(d[68]), "+f"(d[69]), "+f"(d[70]), "+f"(d[71]),
          "+f"(d[72]), "+f"(d[73]), "+f"(d[74]), "+f"(d[75]), "+f"(d[76]), "+f"(d[77]), "+f"(d[78]), "+f"(d[79]),
          "+f"(d[80]), "+f"(d[81]), "+f"(d[82]), "+f"(d[83]), "+f"(d[84]), "+f"(d[85]), "+f"(d[86]), "+f"(d[87]),
          "+f"(d[88]), "+f"(d[89]), "+f"(d[90]), "+f"(d[91]), "+f"(d[92]), "+f"(d[93]), "+f"(d[94]), "+f"(d[95]),
          "+f"(d[96]), "+f"(d[97]), "+f"(d[98]), "+f"(d[99]), "+f"(d[100]), "+f"(d[101]), "+f"(d[102]), "+f"(d[103]),
          "+f"(d[104]), "+f"(d[105]), "+f"(d[106]), "+f"(d[107]), "+f"(d[108]), "+f"(d[109]), "+f"(d[110]), "+f"(d[111])
        : "r"(descA), "r"(descB), "n"(SCALE_D));
}

template <int SCALE_D>
__device__ __forceinline__ void wgmma_ss(float (&d)[64], uint32_t descA, uint32_t descB) {
    asm volatile(
        "{\n.reg .pred p;\n.reg .b64 da, db;\nsetp.ne.b32 p, %66, 0;\n"
        "mov.b64 da, {%64, 0x40000040};\nmov.b64 db, {%65, 0x10};\n"
        "wgmma.mma_async.sync.aligned.m64n128k16.f32.bf16.bf16 "
        "{%0, %1, %2, %3, %4, %5, %6, %7, %8, %9, %10, %11, %12, %13, %14, %15, "
        "%16, %17, %18, %19, %20, %21, %22, %23, %24, %25, %26, %27, %28, %29, %30, %31, "
        "%32, %33, %34, %35, %36, %37, %38, %39, %40, %41, %42, %43, %44, %45, %46, %47, "
        "%48, %49, %50, %51, %52, %53, %54, %55, %56, %57, %58, %59, %60, %61, %62, %63}, "
        "da, db, p, 1, 1, 0, 1;\n}\n"
        : "+f"(d[0]), "+f"(d[1]), "+f"(d[2]), "+f"(d[3]), "+f"(d[4]), "+f"(d[5]), "+f"(d[6]), "+f"(d[7]),
          "+f"(d[8]), "+f"(d[9]), "+f"(d[10]), "+f"(d[11]), "+f"(d[12]), "+f"(d[13]), "+f"(d[14]), "+f"(d[15]),
          "+f"(d[16]), "+f"(d[17]), "+f"(d[18]), "+f"(d[19]), "+f"(d[20]), "+f"(d[21]), "+f"(d[22]), "+f"(d[23]),
          "+f"(d[24]), "+f"(d[25]), "+f"(d[26]), "+f"(d[27]), "+f"(d[28]), "+f"(d[29]), "+f"(d[30]), "+f"(d[31]),
          "+f"(d[32]), "+f"(d[33]), "+f"(d[34]), "+f"(d[35]), "+f"(d[36]), "+f"(d[37]), "+f"(d[38]), "+f"(d[39]),
          "+f"(d[40]), "+f"(d[41]), "+f"(d[42]), "+f"(d[43]), "+f"(d[44]), "+f"(d[45]), "+f"(d[46]), "+f"(d[47]),
          "+f"(d[48]), "+f"(d[49]), "+f"(d[50]), "+f"(d[51]), "+f"(d[52]), "+f"(d[53]), "+f"(d[54]), "+f"(d[55]),
          "+f"(d[56]), "+f"(d[57]), "+f"(d[58]), "+f"(d[59]), "+f"(d[60]), "+f"(d[61]), "+f"(d[62]), "+f"(d[63])
        : "r"(descA), "r"(descB), "n"(SCALE_D));
}

template <int SCALE_D>
__device__ __forceinline__ void wgmma_ss(float (&d)[32], uint32_t descA, uint32_t descB) {
    asm volatile(
        "{\n.reg .pred p;\n.reg .b64 da, db;\nsetp.ne.b32 p, %34, 0;\n"
        "mov.b64 da, {%32, 0x40000040};\nmov.b64 db, {%33, 0x10};\n"
        "wgmma.mma_async.sync.aligned.m64n64k16.f32.bf16.bf16 "
        "{%0, %1, %2, %3, %4, %5, %6, %7, %8, %9, %10, %11, %12, %13, %14, %15, "
        "%16, %17, %18, %19, %20, %21, %22, %23, %24, %25, %26, %27, %28, %29, %30, %31}, "
        "da, db, p, 1, 1, 0, 1;\n}\n"
        : "+f"(d[0]), "+f"(d[1]), "+f"(d[2]), "+f"(d[3]), "+f"(d[4]), "+f"(d[5]), "+f"(d[6]), "+f"(d[7]),
          "+f"(d[8]), "+f"(d[9]), "+f"(d[10]), "+f"(d[11]), "+f"(d[12]), "+f"(d[13]), "+f"(d[14]), "+f"(d[15]),
          "+f"(d[16]), "+f"(d[17]), "+f"(d[18]), "+f"(d[19]), "+f"(d[20]), "+f"(d[21]), "+f"(d[22]), "+f"(d[23]),
          "+f"(d[24]), "+f"(d[25]), "+f"(d[26]), "+f"(d[27]), "+f"(d[28]), "+f"(d[29]), "+f"(d[30]), "+f"(d[31])
        : "r"(descA), "r"(descB), "n"(SCALE_D));
}

template <int SCALE_D>
__device__ __forceinline__ void wgmma_ss(float (&d)[16], uint32_t descA, uint32_t descB) {
    asm volatile(
        "{\n.reg .pred p;\n.reg .b64 da, db;\nsetp.ne.b32 p, %18, 0;\n"
        "mov.b64 da, {%16, 0x40000040};\nmov.b64 db, {%17, 0x10};\n"
        "wgmma.mma_async.sync.aligned.m64n32k16.f32.bf16.bf16 "
        "{%0, %1, %2, %3, %4, %5, %6, %7, %8, %9, %10, %11, %12, %13, %14, %15}, "
        "da, db, p, 1, 1, 0, 1;\n}\n"
        : "+f"(d[0]), "+f"(d[1]), "+f"(d[2]), "+f"(d[3]), "+f"(d[4]), "+f"(d[5]), "+f"(d[6]), "+f"(d[7]),
          "+f"(d[8]), "+f"(d[9]), "+f"(d[10]), "+f"(d[11]), "+f"(d[12]), "+f"(d[13]), "+f"(d[14]), "+f"(d[15])
        : "r"(descA), "r"(descB), "n"(SCALE_D));
}

__device__ __forceinline__ void wgmma_rs(float (&d)[64], const uint4& a, uint32_t descB) {
    asm volatile(
        "{\n.reg .pred p;\n.reg .b64 db;\nsetp.eq.b32 p, 0, 0;\n"
        "mov.b64 db, {%68, 0x10};\n"
        "wgmma.mma_async.sync.aligned.m64n128k16.f32.bf16.bf16 "
        "{%0, %1, %2, %3, %4, %5, %6, %7, %8, %9, %10, %11, %12, %13, %14, %15, "
        "%16, %17, %18, %19, %20, %21, %22, %23, %24, %25, %26, %27, %28, %29, %30, %31, "
        "%32, %33, %34, %35, %36, %37, %38, %39, %40, %41, %42, %43, %44, %45, %46, %47, "
        "%48, %49, %50, %51, %52, %53, %54, %55, %56, %57, %58, %59, %60, %61, %62, %63}, "
        "{%64, %65, %66, %67}, db, p, 1, 1, 1;\n}\n"
        : "+f"(d[0]), "+f"(d[1]), "+f"(d[2]), "+f"(d[3]), "+f"(d[4]), "+f"(d[5]), "+f"(d[6]), "+f"(d[7]),
          "+f"(d[8]), "+f"(d[9]), "+f"(d[10]), "+f"(d[11]), "+f"(d[12]), "+f"(d[13]), "+f"(d[14]), "+f"(d[15]),
          "+f"(d[16]), "+f"(d[17]), "+f"(d[18]), "+f"(d[19]), "+f"(d[20]), "+f"(d[21]), "+f"(d[22]), "+f"(d[23]),
          "+f"(d[24]), "+f"(d[25]), "+f"(d[26]), "+f"(d[27]), "+f"(d[28]), "+f"(d[29]), "+f"(d[30]), "+f"(d[31]),
          "+f"(d[32]), "+f"(d[33]), "+f"(d[34]), "+f"(d[35]), "+f"(d[36]), "+f"(d[37]), "+f"(d[38]), "+f"(d[39]),
          "+f"(d[40]), "+f"(d[41]), "+f"(d[42]), "+f"(d[43]), "+f"(d[44]), "+f"(d[45]), "+f"(d[46]), "+f"(d[47]),
          "+f"(d[48]), "+f"(d[49]), "+f"(d[50]), "+f"(d[51]), "+f"(d[52]), "+f"(d[53]), "+f"(d[54]), "+f"(d[55]),
          "+f"(d[56]), "+f"(d[57]), "+f"(d[58]), "+f"(d[59]), "+f"(d[60]), "+f"(d[61]), "+f"(d[62]), "+f"(d[63])
        : "r"(a.x), "r"(a.y), "r"(a.z), "r"(a.w), "r"(descB));
}

__device__ __forceinline__ void wgmma_rs(float (&d)[32], const uint4& a, uint32_t descB) {
    asm volatile(
        "{\n.reg .pred p;\n.reg .b64 db;\nsetp.eq.b32 p, 0, 0;\n"
        "mov.b64 db, {%36, 0x10};\n"
        "wgmma.mma_async.sync.aligned.m64n64k16.f32.bf16.bf16 "
        "{%0, %1, %2, %3, %4, %5, %6, %7, %8, %9, %10, %11, %12, %13, %14, %15, "
        "%16, %17, %18, %19, %20, %21, %22, %23, %24, %25, %26, %27, %28, %29, %30, %31}, "
        "{%32, %33, %34, %35}, db, p, 1, 1, 1;\n}\n"
        : "+f"(d[0]), "+f"(d[1]), "+f"(d[2]), "+f"(d[3]), "+f"(d[4]), "+f"(d[5]), "+f"(d[6]), "+f"(d[7]),
          "+f"(d[8]), "+f"(d[9]), "+f"(d[10]), "+f"(d[11]), "+f"(d[12]), "+f"(d[13]), "+f"(d[14]), "+f"(d[15]),
          "+f"(d[16]), "+f"(d[17]), "+f"(d[18]), "+f"(d[19]), "+f"(d[20]), "+f"(d[21]), "+f"(d[22]), "+f"(d[23]),
          "+f"(d[24]), "+f"(d[25]), "+f"(d[26]), "+f"(d[27]), "+f"(d[28]), "+f"(d[29]), "+f"(d[30]), "+f"(d[31])
        : "r"(a.x), "r"(a.y), "r"(a.z), "r"(a.w), "r"(descB));
}

__device__ __forceinline__ void wgmma_rs(float (&d)[16], const uint4& a, uint32_t descB) {
    asm volatile(
        "{\n.reg .pred p;\n.reg .b64 db;\nsetp.eq.b32 p, 0, 0;\n"
        "mov.b64 db, {%20, 0x10};\n"
        "wgmma.mma_async.sync.aligned.m64n32k16.f32.bf16.bf16 "
        "{%0, %1, %2, %3, %4, %5, %6, %7, %8, %9, %10, %11, %12, %13, %14, %15}, "
        "{%16, %17, %18, %19}, db, p, 1, 1, 1;\n}\n"
        : "+f"(d[0]), "+f"(d[1]), "+f"(d[2]), "+f"(d[3]), "+f"(d[4]), "+f"(d[5]), "+f"(d[6]), "+f"(d[7]),
          "+f"(d[8]), "+f"(d[9]), "+f"(d[10]), "+f"(d[11]), "+f"(d[12]), "+f"(d[13]), "+f"(d[14]), "+f"(d[15])
        : "r"(a.x), "r"(a.y), "r"(a.z), "r"(a.w), "r"(descB));
}

constexpr int NT = N_ / BN, MT = M_ / BM;
constexpr int W_BYTES = BN * BK * 2;
constexpr int SLAB = 8 * BN * 4;
constexpr int SC_ROW = BN * 2;
constexpr int X_OFF = 0;
constexpr int W_OFF = 10 * 8192;
constexpr int R_OFF = W_OFF + 4 * W_BYTES;
constexpr int SC_OFF = R_OFF + W_BYTES - 2 * SC_ROW;
constexpr int RAW0_OFF = W_OFF + 2 * W_BYTES;
constexpr int SC0_OFF = W_OFF + 3 * W_BYTES;
constexpr int BAR_OFF = SC_OFF + 16 * SC_ROW;
constexpr int SMEM_BYTES = BAR_OFF + 896;
constexpr unsigned READY = MT * 7;
constexpr int UM = 22;
constexpr int NAG = 7;

__device__ __align__(1024) uint8_t g_wimg[(size_t)NT * KC * W_BYTES];
__device__ unsigned g_flag[NT * 32];

__host__ __device__ constexpr int slab_at(int u) { return u == 0 ? 2 : u == 1 ? 3 : u == 3 ? 4 : u == 5 ? 5 : (u >= 7 && u <= 16) ? u - 1 : -1; }
__host__ __device__ constexpr int wload_at(int u) {
    return u <= 10 ? ((u & 1) ? -1 : u / 2 + 1) : u <= 17 ? ((u & 1) ? (u + 3) / 2 : -1) : u == 18 ? 11 : u == 19 ? 12 : u == 20 ? 15 : u == 21 ? 13 : -1;
}
__host__ __device__ constexpr int tail_chunk(int j) { return j == 3 ? 15 : j == 4 ? 14 : 11 + j; }
__host__ __device__ constexpr int wbuf(int c) { return c == 15 ? 4 : c & 3; }

template <int NR>
__device__ __forceinline__ void store_cols(const float (&acc)[NR], uint8_t* p) {
#pragma unroll
    for (int j = 0; j < NR / 16; j++) {
        const int i = 16 * j;
        stg128(p + j * 64, pack_bf16(acc[i], acc[i + 1]), pack_bf16(acc[i + 4], acc[i + 5]), pack_bf16(acc[i + 8], acc[i + 9]), pack_bf16(acc[i + 12], acc[i + 13]));
        stg128(p + j * 64 + 8 * N_ * 2, pack_bf16(acc[i + 2], acc[i + 3]), pack_bf16(acc[i + 6], acc[i + 7]), pack_bf16(acc[i + 10], acc[i + 11]), pack_bf16(acc[i + 14], acc[i + 15]));
    }
}

__global__ void __cluster_dims__(2, 1, 1) __launch_bounds__(256, 1)
nf4_gemm_kernel(const uint8_t* __restrict__ qw, const __nv_bfloat16* __restrict__ cb, const __nv_bfloat16* __restrict__ absmax,
                uint8_t* __restrict__ wimg, unsigned* __restrict__ gflags, uint8_t* __restrict__ out, const unsigned zero,
                const __grid_constant__ CUtensorMap tmx, const __grid_constant__ CUtensorMap tmx64, const __grid_constant__ CUtensorMap tmq16,
                const __grid_constant__ CUtensorMap tmq8, const __grid_constant__ CUtensorMap tmq1, const __grid_constant__ CUtensorMap tms) {
    extern __shared__ __align__(1024) uint8_t smem[];
    const int rank = blockIdx.x & 1;
    const int mt = (blockIdx.x >> 5) * 2 + rank, nt = (blockIdx.x >> 1) & 15;
    const uint8_t* share;
    asm volatile(
        "{\n.reg .b32 t, b, o, h;\n.reg .b64 a;\n.reg .pred p;\n"
        "mov.u32 t, %%tid.x;\nmov.u32 b, %%ctaid.x;\n"
        "shr.u32 h, t, 5;\nshl.b32 o, t, 5;\nmad.lo.u32 o, h, %2 - 1024, o;\n"
        "and.b32 h, b, 1;\nmad.lo.u32 o, h, 8 * %2 - %3 / 2, o;\n"
        "shr.u32 h, b, 5;\nmad.lo.u32 o, h, 16 * %2 - 16 * %3, o;\n"
        "mad.lo.u32 o, b, %3 / 2, o;\n"
        "cvt.u64.u32 a, o;\nadd.u64 a, a, %1;\n"
        "prefetch.global.L2 [a + 64 * %2];\n"
        "setp.lt.u32 p, b, 64;\n@p prefetch.global.L2 [a + 96 * %2];\n"
        "mov.b64 %0, a;\n}\n" : "=l"(share) : "l"(qw), "n"(N_ * 4), "n"(BN * 4));
    const uint32_t sbase = smem_u32(smem);
    const int warp = __shfl_sync(~0u, (int)(threadIdx.x >> 5), 0);
    const int wg = warp >> 2, wj = warp & 3;
    const int lane = threadIdx.x & 31;
    const uint32_t bars = sbase + BAR_OFF;
    const uint32_t snap = bars;
    const uint32_t xfull = bars + 64 + wg * 40;
    const uint32_t wfull = bars + 144;
    const uint32_t wempty = bars + 184;
    const uint32_t ringfull = bars + 216;
    const uint32_t rawbar = bars + 248;
    const uint32_t wown = bars + 264;
    const uint32_t stored = bars + 272 - 8;
    const uint32_t wlast = bars + 344;
    const uint32_t xbase = sbase + X_OFF + wg * 40960, wbase = sbase + W_OFF, rbase = sbase + R_OFF;
    const int xrow = mt * BM + wg * 128 + wj * 16;
    const uint8_t* wsrc = wimg + (size_t)nt * KC * W_BYTES;
    unsigned* flags = gflags + nt * 32;

    auto load_x = [&](int u, int cs = -1) {
        const int c = u < UM ? u >> 1 : tail_chunk((u - UM) % 5), b = u < UM ? u & 1 : (u - UM) / 5;
        mbar_expect_tx(xfull + 8 * (u % 5), cs >= 0 ? 3072 : 2048);
        tma_load_2d(xbase + (u % 5) * 8192 + wj * 2048, &tmx, c * BK, xrow + b * 64, xfull + 8 * (u % 5));
        if (cs >= 0) tma_load_2d(rbase + (cs & 3) * SLAB + warp * 1024, &tmq1, nt * BN + warp * 32, cs * BK + mt * 8, xfull + 8 * (u % 5));
    };
    auto load_x64 = [&](int g, int u) {
        const uint32_t bar = bars + 64 + g * 40 + 8 * u;
        mbar_arrive_n(bar, 3);
        mbar_expect_tx(bar, 8192);
        tma_load_2d(sbase + X_OFF + g * 40960 + u * 8192, &tmx64, (u >> 1) * BK, mt * BM + g * 128 + (u & 1) * 64, bar);
    };
    auto load_slab = [&](int c, uint32_t extra = 0) {
        mbar_expect_tx(ringfull + 8 * (c & 3), SLAB + extra);
        tma_load_3d(rbase + (c & 3) * SLAB, &tmq8, 0, c * BK + mt * 8, nt * 7, ringfull + 8 * (c & 3));
    };
    auto load_raw = [&](int p, uint32_t extra = 0) {
        mbar_expect_tx(rawbar + 8 * p, 2 * SLAB + extra);
        tma_load_3d(sbase + RAW0_OFF + p * 2 * SLAB, &tmq16, 0, rank * 32 + p * 16, nt * 7, rawbar + 8 * p);
    };
    if (warp == 7) {
        if (elect()) {
            mbar_init(ringfull + 8, 1); mbar_init(rawbar, 1); mbar_init(rawbar + 8, 1);
            load_slab(1, SC_ROW);
            bulk_load(sbase + SC0_OFF + SC_ROW, absmax + N_ + nt * BN, SC_ROW, ringfull + 8);
            load_raw(0, SC_ROW);
            bulk_load(sbase + SC0_OFF, absmax + nt * BN, SC_ROW, rawbar);
            load_raw(1);
            mbar_init(bars + 64, 4); mbar_init(bars + 72, 4); mbar_init(bars + 104, 4); mbar_init(bars + 112, 4); mbar_init(ringfull + 16, 1);
            mbar_init_fence();
        }
        __syncwarp();
    }
    uint4 c0, c1;
    asm volatile("ld.global.nc.v4.u32 {%0, %1, %2, %3}, [%8];\nld.global.nc.v4.u32 {%4, %5, %6, %7}, [%8 + 16];"
                 : "=r"(c0.x), "=r"(c0.y), "=r"(c0.z), "=r"(c0.w), "=r"(c1.x), "=r"(c1.y), "=r"(c1.z), "=r"(c1.w) : "l"(cb));
    if (warp < 7) delay(200);
    asm volatile("prefetch.global.L2 [%0];" ::"l"(share));
    if (blockIdx.x < 64) asm volatile("prefetch.global.L2 [%0];" ::"l"(share + 32 * N_ * 4));
    if (warp == 5 || warp == 6) {
        if (elect()) {
            if (warp == 6) {
#pragma unroll
                for (int s = 0; s < 5; s++) mbar_init(wfull + 8 * s, 1);
#pragma unroll
                for (int s = 0; s < 4; s++) mbar_init(wempty + 8 * s, 16);
                mbar_init(wown, 7); mbar_init(wlast, 1); mbar_init(ringfull, 1); mbar_init(ringfull + 24, 1);
                mbar_expect_tx(wfull, W_BYTES / 2);
            }
            if (warp == 5) {
#pragma unroll
                for (int s = 0; s < 10; s++) if (s % 5 >= 2) mbar_init(bars + 64 + 8 * s, 4);
#pragma unroll
                for (int s = 1; s <= NAG; s++) mbar_init(stored + 8 * s, s == 1 ? 7 : 224);
            }
            mbar_init_fence();
        }
        __syncwarp();
    }
    cluster_arrive();
    if (warp == 7) {
        if (elect()) { load_x64(0, 0); load_x64(0, 1); load_x64(1, 0); load_x64(1, 1); }
        __syncwarp();
    }
    const uint32_t rlane = (lane & 7) * 128 + ((((lane >> 3) * 2) ^ (lane & 7)) << 4);
    const uint32_t wlane = warp * 1024 + (lane & 7) * 16 + (lane >> 3) * 4;
    const uint32_t slabsrc = __shfl_sync(~0u, (warp < 7 ? warp * 1024 + rlane : 0) + sbase, lane);
    const uint32_t scsrc = __shfl_sync(~0u, sbase + (warp < 7 ? warp * 64 : 0) + (lane >> 3) * 16, lane);
    uint8_t* const gdst = wimg + (size_t)nt * KC * W_BYTES + (mt >> 1) * SLAB + (mt & 1) * 128 + wlane;
    uint8_t* const gkeep = (uint8_t*)__shfl_sync(~0u, (unsigned long long)gdst, lane);
    uint8_t* const gread = (uint8_t*)__shfl_sync(~0u, (unsigned long long)(warp < 7 ? gdst + (lane >> 3) * 252 : (uint8_t*)flags + (lane >> 3) * 16), lane);
    Lut lut = {};
    if (warp < 7) {
        lut.lo[0] = __byte_perm(c0.x, c0.y, 0x6420); lut.hi[0] = __byte_perm(c0.x, c0.y, 0x7531);
        lut.lo[1] = __byte_perm(c0.z, c0.w, 0x6420); lut.hi[1] = __byte_perm(c0.z, c0.w, 0x7531);
        lut.lo[2] = __byte_perm(c1.x, c1.y, 0x6420); lut.hi[2] = __byte_perm(c1.x, c1.y, 0x7531);
        lut.lo[3] = __byte_perm(c1.z, c1.w, 0x6420); lut.hi[3] = __byte_perm(c1.z, c1.w, 0x7531);
    }
    cluster_wait();

    auto store_slab = [&](int c, uint32_t p, const uint4& sc) {
        const uint4 w = dequant8(p, sc, lut);
        uint8_t* g = gkeep + (size_t)c * W_BYTES;
        stg32(g, w.x); stg32(g + 256, w.y); stg32(g + 512, w.z); stg32(g + 768, w.w);
        if (c == 1) {
            __syncwarp();
            if (elect()) mbar_arrive(stored + 8);
            __syncwarp();
        } else {
            read_l2(scsrc + SC_OFF + SC_ROW * c, gread + (size_t)c * W_BYTES, (lane & 7) == 0);
            if (c <= NAG) read_arrive(stored + 8 * c);
        }
    };
    auto take_sample = [&]() { read_l2(scsrc + BAR_OFF, gread, (lane & 7) == 0); };
    auto load_w = [&](int c) {
        read_wait<0>();
        poll_ge(flags + c, lds32(snap + 4 * c), READY);
        asm volatile("fence.acquire.gpu;" ::: "memory");
        asm volatile("fence.proxy.async.global;" ::: "memory");
        if (c >= 4 && c < 15) mbar_wait(wempty + 8 * (c & 3), ((c >> 2) - 1) & 1);
        if (elect()) {
            if (c == 1) {
                mbar_expect_tx(wfull + 8, W_BYTES / 2);
                bulk_load_mc(wbase + W_BYTES + rank * SLAB, wsrc + W_BYTES + rank * SLAB, SLAB, wfull + 8);
                mbar_expect_tx(wlast, W_BYTES / 2);
                bulk_load_mc(wbase + W_BYTES + (2 + rank) * SLAB, wsrc + W_BYTES + (2 + rank) * SLAB, SLAB, wlast);
            } else {
                mbar_expect_tx(wfull + 8 * wbuf(c), W_BYTES);
                bulk_load_mc(wbase + wbuf(c) * W_BYTES + rank * (W_BYTES / 2), wsrc + (size_t)c * W_BYTES + rank * (W_BYTES / 2), W_BYTES / 2, wfull + 8 * wbuf(c));
            }
        }
        __syncwarp();
    };

    if (warp < 7) {
        mbar_wait(ringfull + 8, 0);
        store_slab(1, pack8(lds128(slabsrc + R_OFF + SLAB), lds128((slabsrc ^ 16) + R_OFF + SLAB)), lds128(scsrc + SC0_OFF + SC_ROW));
        const uint32_t tab = prmt(prmt(lane & 8 ? lut.lo[2] : lut.lo[0], lane & 8 ? lut.lo[3] : lut.lo[1], lane & 7),
                                  prmt(lane & 8 ? lut.hi[2] : lut.hi[0], lane & 8 ? lut.hi[3] : lut.hi[1], lane & 7), 0x40);
        uint4 sc;
#pragma unroll
        for (int p = 0; p < 2; p++) {
            mbar_wait(rawbar + 8 * p, 0);
            if (p == 0) { sc = lds128(scsrc + SC0_OFF); }
            const uint32_t a = sbase + RAW0_OFF + p * 2 * SLAB + warp * 2048;
            const uint4 v0 = lds128(a + rlane), v1 = lds128(a + (rlane ^ 16)), v2 = lds128(a + rlane + 1024), v3 = lds128(a + (rlane ^ 16) + 1024);
            const uint4 w0 = dequant8(pack8(v0, v1), sc, lut), w1 = dequant8_shfl(v2, v3, sc, tab);
            const uint32_t d = wbase + (2 * rank + p) * SLAB, e = d + wlane;
            sts32(e, w0.x); sts32(e + 256, w0.y); sts32(e + 512, w0.z); sts32(e + 768, w0.w);
            sts32(e + 128, w1.x); sts32(e + 384, w1.y); sts32(e + 640, w1.z); sts32(e + 896, w1.w);
            fence_async_smem();
            __syncwarp();
            if (elect()) {
                if (p == 1) mbar_arrive(wown);
                copy_to_peer(d + warp * 1024, 1024, wfull, rank ^ 1);
            }
            __syncwarp();
        }
    } else {
        mbar_wait(stored + 8, 0);
        const unsigned v = ld_relaxed(wsrc + W_BYTES + (mt >> 1) * SLAB + (mt & 1) * 128 + (lane < 28 ? lane : 0) * 256);
        if (elect()) {
            load_slab(2, 14 * SC_ROW);
            tma_load_2d(sbase + SC_OFF + 2 * SC_ROW, &tms, nt * BN, 2, ringfull + 16);
        }
        __syncwarp();
        const unsigned n = after(7, v, zero);
        __syncwarp();
        if (elect()) red_add(flags + 1, n);
        __syncwarp();
        if (elect()) { load_x64(0, 2); load_x64(1, 2); load_x64(0, 3); load_x64(1, 3); load_slab(3); }
        __syncwarp();
    }

    float acc0[112], acc1[112];
    const uint32_t descA = ((xbase & 0x3FFFF) >> 4) | (1u << 16), descB = ((wbase & 0x3FFFF) >> 4) | ((128u >> 4) << 16);
    static_for<0, UM>([&](auto U) __attribute__((always_inline)) {
        constexpr int u = U.value, kc = u >> 1;
        constexpr int c = slab_at(u);
        uint32_t da = descA, db = descB;
        asm volatile("" : "+r"(da), "+r"(db));
        uint4 q0, q1, sc;
        auto slab_loads = [&]() {
            q0 = lds128(slabsrc + R_OFF + (c & 3) * SLAB); q1 = lds128((slabsrc ^ 16) + R_OFF + (c & 3) * SLAB);
            sc = lds128(scsrc + SC_OFF + SC_ROW * c);
        };
        if (u < 4) {
            if (u == 0) mbar_wait3(xfull, 0, xfull + 8, 0, wown, 0);
            if (u == 1) mbar_wait(wfull, 0);
            if (u == 2) mbar_wait3(xfull + 16, 0, xfull + 24, 0, wfull + 8, 0);
            if (u == 3) { mbar_wait2(wlast, 0, ringfull, 0); slab_loads(); }
            if (u == 0 && warp == 7) take_sample();
            const int h = u < 2 ? rank ^ u : u & 1;
            da += kc * 1024 + h * 4; db += kc * (W_BYTES >> 4) + h * (2 * SLAB >> 4);
            wgmma_fence();
            wgmma_ss<u != 0>(acc0, da, db); wgmma_ss<u != 0>(acc1, da + 512, db);
            wgmma_ss<1>(acc0, da + 2, db + (SLAB >> 4)); wgmma_ss<1>(acc1, da + 514, db + (SLAB >> 4));
        } else {
            if (u & 1) mbar_wait(xfull + 8 * (u % 5), (u / 5) & 1);
            else mbar_wait2(xfull + 8 * (u % 5), (u / 5) & 1, wfull + 8 * (kc & 3), (kc >> 2) & 1);
            if (c >= 0) slab_loads();
            da += (u % 5) * 512; db += (kc & 3) * (W_BYTES >> 4);
            wgmma_fence();
#pragma unroll
            for (int ks = 0; ks < 4; ks++) {
                if (u & 1) wgmma_ss<1>(acc1, da + ks * 2, db + ks * (SLAB >> 4));
                else wgmma_ss<1>(acc0, da + ks * 2, db + ks * (SLAB >> 4));
            }
        }
        wgmma_commit();
        if (u >= 2) wgmma_wait<1>();
        if (warp < 7) {
            constexpr int cp = slab_at(u - 2) > NAG ? slab_at(u - 2) : -1;
            if (u < 2) { mbar_wait(ringfull + 8 * c, 0); slab_loads(); }
            uint32_t p = 0;
            if (c >= 0) p = pack8(q0, q1);
            if (cp >= 0) { if (slab_at(u - 1) >= 0) read_wait<1>(); else read_wait<0>(); }
            if (u >= 2) {
                if (elect()) {
                    if (u <= 17) load_x(u + 3, slab_at(u + 3));
                    if (u >= 17) load_x(u + 4);
                    if (!(u & 1)) mbar_arrive_both(wempty + 8 * ((kc - 1) & 3));
                    if (cp >= 0) red_add(flags + cp, 1);
                }
                __syncwarp();
            }
            if (c >= 0) store_slab(c, p, sc);
        } else {
            constexpr int cw = wload_at(u), cc = slab_at(u - 1) <= NAG ? slab_at(u - 1) : -1;
            if (cw >= 0 && cw <= 6) load_w(cw);
            if (u != 1) {
                if (elect()) {
                    if (u == 0) load_slab(4);
                    if (u >= 2 && u <= 17) load_x(u + 3);
                    if (u >= 17) load_x(u + 4);
                    if (u >= 2 && !(u & 1)) mbar_arrive_both(wempty + 8 * ((kc - 1) & 3));
                }
                __syncwarp();
            }
            if (cc >= 0) {
                mbar_wait(stored + 8 * cc, 0);
                if (elect()) red_add(flags + cc, 7);
                __syncwarp();
            }
            if (u == 1) {
                if (elect()) { load_x64(0, 4); load_x64(1, 4); }
                __syncwarp();
                delay(300);
            }
            if (cw > 6) load_w(cw);
            if (wload_at(u + 1) >= 0) take_sample();
        }
    });

    uint32_t tA = descA, tB = descB;
    asm volatile("" : "+r"(tA), "+r"(tB));
    if (wg == 1) {
        wgmma_wait<0>();
        if (elect()) { load_x(UM + 4); mbar_arrive_both(wempty + 16); }
        __syncwarp();
        if (warp == 7) load_w(14);
        if (warp == 7 && lane == 0) {
            if (atomicAdd(flags + 16, 1) == MT - 1) {
#pragma unroll
                for (int c = 0; c <= 16; c++) flags[c] = 0;
            }
        }
        __syncwarp();
        bar_sync<256>(1);
    }
#pragma unroll
    for (int j = 0; j < 5; j++) {
        const int c = tail_chunk(j), v = UM + j;
        mbar_wait2(xfull + 8 * (v % 5), (v / 5) & 1, wfull + 8 * wbuf(c), c == 15 ? 0 : (c >> 2) & 1);
        wgmma_fence();
#pragma unroll
        for (int ks = 0; ks < 4; ks++) wgmma_ss<1>(acc0, tA + (v % 5) * 512 + ks * 2, tB + wbuf(c) * (W_BYTES >> 4) + ks * (SLAB >> 4));
        wgmma_commit();
        if (j == 4) bar_arrive<256>(1 + wg);
        if (j == 0) {
            if (wg == 0) {
                wgmma_wait<1>();
                if (elect()) { load_x(UM + 4); mbar_arrive_both(wempty + 16); }
                __syncwarp();
            }
        } else if (j >= 2) {
            wgmma_wait<2>();
            if (elect()) load_x(v + 3);
            __syncwarp();
        }
    }
    wgmma_wait<1>();
    if (elect()) load_x(UM + 8);
    __syncwarp();
    wgmma_wait<0>();
    if (elect()) load_x(UM + 9);
    __syncwarp();
    uint8_t* optr = out + (size_t)(xrow + (lane >> 2)) * (N_ * 2) + nt * (BN * 2) + (lane & 3) * 16;
    float pa[64], pb[32], pc[16];
#pragma unroll
    for (int i = 0; i < 64; i++) asm volatile("mov.b32 %0, %1;" : "=f"(pa[i]) : "f"(acc1[i]));
#pragma unroll
    for (int i = 0; i < 32; i++) asm volatile("mov.b32 %0, %1;" : "=f"(pb[i]) : "f"(acc1[64 + i]));
#pragma unroll
    for (int i = 0; i < 16; i++) asm volatile("mov.b32 %0, %1;" : "=f"(pc[i]) : "f"(acc1[96 + i]));
    uint4 af[16];
    uint32_t pk[56];
    auto store_pk = [&](int h0, int h1) {
#pragma unroll
        for (int h = h0; h < h1; h++) {
            const int i = 8 * (h >> 1) + (h & 1);
            stg128(optr + (h >> 1) * 64 + (h & 1) * (8 * N_ * 2), pk[i], pk[i + 2], pk[i + 4], pk[i + 6]);
        }
    };
    const uint32_t alane = xbase + wj * 2048 + (lane & 15) * 128 + (((lane >> 4) ^ (lane & 7)) << 4);
    static_for<0, 4>([&](auto J) __attribute__((always_inline)) {
        constexpr int j = J.value, v = UM + 5 + j;
        mbar_wait(xfull + 8 * (v % 5), (v / 5) & 1);
#pragma unroll
        for (int ks = 0; ks < 4; ks++) af[4 * j + ks] = ldmatrix_x4((alane ^ (ks * 32)) + (v % 5) * 8192);
#pragma unroll
        for (int i = 16 * j; i < (j < 3 ? 16 * j + 16 : 56); i++) pk[i] = pack_bf16(acc0[2 * i], acc0[2 * i + 1]);
        store_pk(2 * j, 2 * j + 2);
    });
    store_pk(8, 10);
    if (wg == 0) store_pk(10, 14);
    auto piece = [&](auto& d, int cb) {
        wgmma_fence();
#pragma unroll
        for (int j = 0; j < 5; j++) {
            if (cb == 0 && j == 4) { mbar_wait(xfull + 8 * ((UM + 9) % 5), ((UM + 9) / 5) & 1); wgmma_fence(); }
#pragma unroll
            for (int ks = 0; ks < 4; ks++) {
                const uint32_t db = tB + wbuf(tail_chunk(j)) * (W_BYTES >> 4) + ks * (SLAB >> 4) + cb * 64;
                if (j < 4) wgmma_rs(d, af[(4 * j + ks) & 15], db);
                else wgmma_ss<1>(d, tA + ((UM + 9) % 5) * 512 + ks * 2, db);
            }
        }
        wgmma_commit();
    };
    bar_sync<256>(2 + wg);
    piece(pa, 0);
    bar_arrive<256>(3 + wg);
    if (wg == 1) store_pk(10, 14);
    wgmma_wait<0>();
    optr += 64 * N_ * 2;
    store_cols(pa, optr);
    bar_sync<256>(4 + wg);
    piece(pb, 4);
    bar_arrive<256>(5 + wg);
    wgmma_wait<0>();
    store_cols(pb, optr + 4 * 64);
    bar_sync<256>(6 + wg);
    piece(pc, 6);
    if (wg == 0) bar_arrive<256>(7);
    cluster_arrive();
    wgmma_wait<0>();
    store_cols(pc, optr + 6 * 64);
    cluster_wait();
}

typedef CUresult (*EncodeFn)(CUtensorMap*, CUtensorMapDataType, cuuint32_t, void*, const cuuint64_t*, const cuuint64_t*,
                             const cuuint32_t*, const cuuint32_t*, CUtensorMapInterleave, CUtensorMapSwizzle,
                             CUtensorMapL2promotion, CUtensorMapFloatOOBfill);

extern "C" void kernel_launch(void* const* d_in, const int* in_sizes, int n_in, void* d_out, int out_size) {
    static EncodeFn encode = nullptr;
    static void *wimg = nullptr, *gflags = nullptr;
    if (!encode) {
        cudaGetSymbolAddress(&wimg, g_wimg);
        cudaGetSymbolAddress(&gflags, g_flag);
        void* fn = nullptr;
        cudaDriverEntryPointQueryResult qr;
        cudaGetDriverEntryPoint("cuTensorMapEncodeTiled", &fn, cudaEnableDefault, &qr);
        encode = (EncodeFn)fn;
        cudaFuncSetAttribute(nf4_gemm_kernel, cudaFuncAttributeMaxDynamicSharedMemorySize, SMEM_BYTES);
    }
    void *x = d_in[0], *qw = d_in[1], *cb = d_in[2], *absmax = d_in[3];
    auto map = [&](CUtensorMapDataType t, int rank, void* p, const cuuint64_t* dims, const cuuint64_t* strides, const cuuint32_t* box, bool swizzle) {
        CUtensorMap m;
        const cuuint32_t es[3] = {1, 1, 1};
        encode(&m, t, rank, p, dims, strides, box, es, CU_TENSOR_MAP_INTERLEAVE_NONE,
               swizzle ? CU_TENSOR_MAP_SWIZZLE_128B : CU_TENSOR_MAP_SWIZZLE_NONE,
               swizzle ? CU_TENSOR_MAP_L2_PROMOTION_L2_128B : CU_TENSOR_MAP_L2_PROMOTION_NONE, CU_TENSOR_MAP_FLOAT_OOB_FILL_NONE);
        return m;
    };
    const cuuint64_t xd[2] = {K_, M_}, xs[1] = {K_ * 2};
    const cuuint64_t q3d[3] = {32, K_, N_ / 32}, q3s[2] = {N_ * 4, 128};
    const cuuint64_t q2d[2] = {N_, K_}, q2s[1] = {N_ * 4};
    const cuuint64_t sd[2] = {N_, KC}, ss[1] = {N_ * 2};
    const cuuint32_t bx[2] = {BK, 16}, bx64[2] = {BK, 64}, bq16[3] = {32, 16, 7}, bq8[3] = {32, 8, 7}, bq1[2] = {32, 8}, bs[2] = {BN, KC - 2};
    nf4_gemm_kernel<<<128, 256, SMEM_BYTES>>>(
        (const uint8_t*)qw, (const __nv_bfloat16*)cb, (const __nv_bfloat16*)absmax, (uint8_t*)wimg, (unsigned*)gflags, (uint8_t*)d_out, 0u,
        map(CU_TENSOR_MAP_DATA_TYPE_BFLOAT16, 2, x, xd, xs, bx, true), map(CU_TENSOR_MAP_DATA_TYPE_BFLOAT16, 2, x, xd, xs, bx64, true),
        map(CU_TENSOR_MAP_DATA_TYPE_INT32, 3, qw, q3d, q3s, bq16, true), map(CU_TENSOR_MAP_DATA_TYPE_INT32, 3, qw, q3d, q3s, bq8, true),
        map(CU_TENSOR_MAP_DATA_TYPE_INT32, 2, qw, q2d, q2s, bq1, true), map(CU_TENSOR_MAP_DATA_TYPE_BFLOAT16, 2, absmax, sd, ss, bs, false));
}
```

```cpp
#include <cuda_runtime.h>
#include <cuda_bf16.h>
#include <cuda.h>
#include <stdint.h>

constexpr int M_ = 2048, K_ = 1024, N_ = 3584;
constexpr int BM = 256, BN = 224, BK = 64;
constexpr int KC = K_ / BK;

__device__ __forceinline__ uint32_t smem_u32(const void* p) { return (uint32_t)__cvta_generic_to_shared(p); }
__device__ __forceinline__ bool elect() {
    uint32_t ok;
    asm volatile("{\n.reg .pred p;\nelect.sync _|p, 0xffffffff;\nselp.u32 %0, 1, 0, p;\n}\n" : "=r"(ok));
    return ok != 0;
}
template <int I> struct IC { static constexpr int value = I; };
template <int I, int N, class F> __device__ __forceinline__ void static_for(F&& f) {
    if constexpr (I < N) { f(IC<I>{}); static_for<I + 1, N>(f); }
}

__device__ __forceinline__ void mbar_init(uint32_t bar, uint32_t cnt) { asm volatile("mbarrier.init.shared::cta.b64 [%0], %1;" ::"r"(bar), "r"(cnt) : "memory"); }
__device__ __forceinline__ void mbar_init_fence() { asm volatile("fence.mbarrier_init.release.cluster;" ::: "memory"); }
__device__ __forceinline__ void mbar_expect_tx(uint32_t bar, uint32_t bytes) { asm volatile("mbarrier.arrive.expect_tx.shared::cta.b64 _, [%0], %1;" ::"r"(bar), "r"(bytes) : "memory"); }
__device__ __forceinline__ void mbar_arrive(uint32_t bar) { asm volatile("mbarrier.arrive.shared::cta.b64 _, [%0];" ::"r"(bar) : "memory"); }
__device__ __forceinline__ void mbar_arrive_n(uint32_t bar, uint32_t n) { asm volatile("mbarrier.arrive.shared::cta.b64 _, [%0], %1;" ::"r"(bar), "r"(n) : "memory"); }
__device__ __forceinline__ void mbar_arrive_both(uint32_t bar) {
    asm volatile("{\n.reg .b32 ra;\nmapa.shared::cluster.u32 ra, %0, 0;\nmbarrier.arrive.shared::cluster.b64 _, [ra];\n"
                 "mapa.shared::cluster.u32 ra, %0, 1;\nmbarrier.arrive.shared::cluster.b64 _, [ra];\n}\n" ::"r"(bar) : "memory");
}
#define MBAR_TRY(p, b, q) "mbarrier.try_wait.parity.shared::cta.b64 " p ", [" b "], " q ";\n"
#define MBAR_WAIT(TRY) \
    "{\n.reg .pred p0, p1, p2;\n.reg .b32 n;\n" TRY "@p0 bra LAB_DONE;\nmov.b32 n, 0;\nLAB_WAIT:\n" TRY \
    "@p0 bra LAB_DONE;\nadd.u32 n, n, 1;\nsetp.lt.u32 p0, n, 0x40000;\n@p0 bra LAB_WAIT;\ntrap;\nLAB_DONE:\n}\n"
__device__ __forceinline__ void mbar_wait(uint32_t b0, uint32_t q0) {
    asm volatile(MBAR_WAIT(MBAR_TRY("p0", "%0", "%1")) ::"r"(b0), "r"(q0) : "memory");
}
__device__ __forceinline__ void mbar_wait2(uint32_t b0, uint32_t q0, uint32_t b1, uint32_t q1) {
    asm volatile(MBAR_WAIT(MBAR_TRY("p0", "%0", "%1") MBAR_TRY("p1", "%2", "%3") "and.pred p0, p0, p1;\n")
                 ::"r"(b0), "r"(q0), "r"(b1), "r"(q1) : "memory");
}
__device__ __forceinline__ void mbar_wait3(uint32_t b0, uint32_t q0, uint32_t b1, uint32_t q1, uint32_t b2, uint32_t q2) {
    asm volatile(MBAR_WAIT(MBAR_TRY("p0", "%0", "%1") MBAR_TRY("p1", "%2", "%3") MBAR_TRY("p2", "%4", "%5") "and.pred p0, p0, p1;\nand.pred p0, p0, p2;\n")
                 ::"r"(b0), "r"(q0), "r"(b1), "r"(q1), "r"(b2), "r"(q2) : "memory");
}
__device__ __forceinline__ void cluster_arrive() { asm volatile("barrier.cluster.arrive.relaxed.aligned;" ::: "memory"); }
__device__ __forceinline__ void cluster_wait() { asm volatile("barrier.cluster.wait.acquire.aligned;" ::: "memory"); }
template <int NTHR> __device__ __forceinline__ void bar_arrive(int id) { asm volatile("bar.arrive %0, %1;" ::"r"(id), "n"(NTHR) : "memory"); }
template <int NTHR> __device__ __forceinline__ void bar_sync(int id) { asm volatile("bar.sync %0, %1;" ::"r"(id), "n"(NTHR) : "memory"); }
__device__ __forceinline__ void delay(unsigned clks) {
    asm volatile(
        "{\n.reg .pred p;\n.reg .b32 t0, t;\n"
        "mov.u32 t0, %%clock;\n"
        "LAB_DELAY:\n"
        "mov.u32 t, %%clock;\n"
        "sub.u32 t, t, t0;\n"
        "setp.lt.u32 p, t, %0;\n"
        "vote.sync.any.pred p, p, 0xffffffff;\n"
        "@p bra.uni LAB_DELAY;\n}\n" ::"r"(clks) : "memory");
}

__device__ __forceinline__ void tma_load_2d(uint32_t dst, const CUtensorMap* tm, int c0, int c1, uint32_t bar) {
    asm volatile("cp.async.bulk.tensor.2d.shared::cluster.global.mbarrier::complete_tx::bytes [%0], [%1, {%2, %3}], [%4];"
                 ::"r"(dst), "l"(tm), "r"(c0), "r"(c1), "r"(bar) : "memory");
}
__device__ __forceinline__ void tma_load_3d(uint32_t dst, const CUtensorMap* tm, int c0, int c1, int c2, uint32_t bar) {
    asm volatile("cp.async.bulk.tensor.3d.shared::cluster.global.mbarrier::complete_tx::bytes [%0], [%1, {%2, %3, %4}], [%5];"
                 ::"r"(dst), "l"(tm), "r"(c0), "r"(c1), "r"(c2), "r"(bar) : "memory");
}
__device__ __forceinline__ void bulk_load(uint32_t dst, const void* src, uint32_t bytes, uint32_t bar) {
    asm volatile("cp.async.bulk.shared::cluster.global.mbarrier::complete_tx::bytes [%0], [%1], %2, [%3];"
                 ::"r"(dst), "l"(src), "r"(bytes), "r"(bar) : "memory");
}
__device__ __forceinline__ void bulk_load_mc(uint32_t dst, const void* src, uint32_t bytes, uint32_t bar) {
    asm volatile("cp.async.bulk.shared::cluster.global.mbarrier::complete_tx::bytes.multicast::cluster [%0], [%1], %2, [%3], %4;"
                 ::"r"(dst), "l"(src), "r"(bytes), "r"(bar), "h"((uint16_t)3) : "memory");
}
__device__ __forceinline__ uint32_t mapa(uint32_t addr, uint32_t cta) {
    uint32_t r; asm("mapa.shared::cluster.u32 %0, %1, %2;" : "=r"(r) : "r"(addr), "r"(cta)); return r;
}
__device__ __forceinline__ void copy_to_peer(uint32_t addr, uint32_t bytes, uint32_t bar, uint32_t peer) {
    asm volatile("cp.async.bulk.shared::cluster.shared::cta.mbarrier::complete_tx::bytes [%0], [%1], %2, [%3];"
                 ::"r"(mapa(addr, peer)), "r"(addr), "r"(bytes), "r"(mapa(bar, peer)) : "memory");
}
__device__ __forceinline__ void fence_async_smem() { asm volatile("fence.proxy.async.shared::cta;" ::: "memory"); }

__device__ __forceinline__ uint4 lds128(uint32_t a) {
    uint4 v; asm volatile("ld.shared.v4.b32 {%0, %1, %2, %3}, [%4];" : "=r"(v.x), "=r"(v.y), "=r"(v.z), "=r"(v.w) : "r"(a) : "memory"); return v;
}
__device__ __forceinline__ uint32_t lds32(uint32_t a) {
    uint32_t v; asm volatile("ld.shared.b32 %0, [%1];" : "=r"(v) : "r"(a) : "memory"); return v;
}
__device__ __forceinline__ uint4 ldmatrix_x4(uint32_t a) {
    uint4 v;
    asm volatile("ldmatrix.sync.aligned.m8n8.x4.shared.b16 {%0, %1, %2, %3}, [%4];" : "=r"(v.x), "=r"(v.y), "=r"(v.z), "=r"(v.w) : "r"(a) : "memory");
    return v;
}
__device__ __forceinline__ void sts32(uint32_t a, uint32_t v) { asm volatile("st.shared.b32 [%0], %1;" ::"r"(a), "r"(v) : "memory"); }
__device__ __forceinline__ void stg32(void* p, uint32_t v) { asm volatile("st.global.b32 [%0], %1;" ::"l"(p), "r"(v) : "memory"); }
__device__ __forceinline__ void stg128(void* p, uint32_t a, uint32_t b, uint32_t c, uint32_t d) {
    asm volatile("st.global.v4.b32 [%0], {%1, %2, %3, %4};" ::"l"(p), "r"(a), "r"(b), "r"(c), "r"(d) : "memory");
}

__device__ __forceinline__ unsigned ld_relaxed(const void* p) {
    unsigned v; asm volatile("ld.relaxed.gpu.global.u32 %0, [%1];" : "=r"(v) : "l"(p) : "memory"); return v;
}
__device__ __forceinline__ void read_l2(uint32_t dst, const void* src, uint32_t on) {
    asm volatile("{\n.reg .pred p;\nsetp.ne.u32 p, %2, 0;\n@p cp.async.cg.shared.global [%0], [%1], 16;\n}\ncp.async.commit_group;" ::"r"(dst), "l"(src), "r"(on) : "memory");
}
template <int N> __device__ __forceinline__ void read_wait() { asm volatile("cp.async.wait_group %0;" ::"n"(N) : "memory"); __syncwarp(); }
__device__ __forceinline__ void read_arrive(uint32_t bar) { asm volatile("cp.async.mbarrier.arrive.noinc.shared::cta.b64 [%0];" ::"r"(bar) : "memory"); }
__device__ __forceinline__ unsigned after(unsigned n, unsigned p, unsigned z) {
    unsigned r; asm volatile("lop3.b32 %0, %1, %2, %3, 0xea;" : "=r"(r) : "r"(p), "r"(z), "r"(n)); return r;
}
__device__ __forceinline__ void red_add(unsigned* f, unsigned n) { asm volatile("red.relaxed.gpu.global.add.u32 [%0], %1;" ::"l"(f), "r"(n) : "memory"); }
__device__ __forceinline__ void poll_ge(const unsigned* f, unsigned v, unsigned ready) {
    asm volatile(
        "{\n.reg .pred p;\n.reg .b32 v, n;\n"
        "setp.lt.u32 p, %1, %2;\n"
        "vote.sync.any.pred p, p, 0xffffffff;\n"
        "@!p bra.uni LAB_DONE;\n"
        "mov.b32 n, 0;\n"
        "LAB_POLL:\n"
        "ld.relaxed.gpu.global.u32 v, [%0];\n"
        "setp.lt.u32 p, v, %2;\n"
        "vote.sync.any.pred p, p, 0xffffffff;\n"
        "@!p bra.uni LAB_DONE;\n"
        "add.u32 n, n, 1;\n"
        "setp.lt.u32 p, n, 0x400000;\n"
        "@p bra.uni LAB_POLL;\n"
        "LAB_DONE:\n}\n" ::"l"(f), "r"(v), "r"(ready) : "memory");
}

__device__ __forceinline__ uint32_t pack_bf16(float lo, float hi) {
    uint32_t r; asm("cvt.rn.bf16x2.f32 %0, %1, %2;" : "=r"(r) : "f"(hi), "f"(lo)); return r;
}
__device__ __forceinline__ uint32_t mul_bf16x2(uint32_t a, uint32_t b) { uint32_t r; asm("mul.rn.bf16x2 %0, %1, %2;" : "=r"(r) : "r"(a), "r"(b)); return r; }
__device__ __forceinline__ uint32_t prmt(uint32_t a, uint32_t b, uint32_t s) { uint32_t r; asm("prmt.b32 %0, %1, %2, %3;" : "=r"(r) : "r"(a), "r"(b), "r"(s)); return r; }
__device__ __forceinline__ uint32_t madi(uint32_t hi, uint32_t m, uint32_t lo) { uint32_t r; asm("mad.lo.u32 %0, %1, %2, %3;" : "=r"(r) : "r"(hi), "r"(m), "r"(lo)); return r; }
__device__ __forceinline__ uint32_t pack8(const uint4& a, const uint4& b) {
    return madi(madi(madi(b.w, 65536, a.w), 16, madi(b.z, 65536, a.z)), 256, madi(madi(b.y, 65536, a.y), 16, madi(b.x, 65536, a.x)));
}
struct Lut { uint32_t lo[4], hi[4]; };
__device__ __forceinline__ void lookup4(uint32_t s7, uint32_t sel, const Lut& t, uint32_t& w01, uint32_t& w23) {
    const uint32_t lo = prmt(prmt(t.lo[0], t.lo[1], s7), prmt(t.lo[2], t.lo[3], s7), sel);
    const uint32_t hi = prmt(prmt(t.hi[0], t.hi[1], s7), prmt(t.hi[2], t.hi[3], s7), sel);
    w01 = prmt(lo, hi, 0x5140);
    w23 = prmt(lo, hi, 0x7362);
}
__device__ __forceinline__ uint4 dequant8(uint32_t p, const uint4& sc, const Lut& t) {
    const uint32_t m8 = p & 0x88888888u, s7 = p & 0x77777777u;
    uint4 r;
    lookup4(s7, (m8 >> 1) + 0x3210u, t, r.x, r.y);
    lookup4(s7 >> 16, (m8 >> 17) + 0x3210u, t, r.z, r.w);
    r.x = mul_bf16x2(r.x, sc.x); r.y = mul_bf16x2(r.y, sc.y); r.z = mul_bf16x2(r.z, sc.z); r.w = mul_bf16x2(r.w, sc.w);
    return r;
}
__device__ __forceinline__ uint4 dequant8_shfl(const uint4& q0, const uint4& q1, const uint4& sc, uint32_t tab) {
    uint4 r;
    r.x = mul_bf16x2(__byte_perm(__shfl_sync(~0u, tab, q0.x), __shfl_sync(~0u, tab, q0.y), 0x5410), sc.x);
    r.y = mul_bf16x2(__byte_perm(__shfl_sync(~0u, tab, q0.z), __shfl_sync(~0u, tab, q0.w), 0x5410), sc.y);
    r.z = mul_bf16x2(__byte_perm(__shfl_sync(~0u, tab, q1.x), __shfl_sync(~0u, tab, q1.y), 0x5410), sc.z);
    r.w = mul_bf16x2(__byte_perm(__shfl_sync(~0u, tab, q1.z), __shfl_sync(~0u, tab, q1.w), 0x5410), sc.w);
    return r;
}

__device__ __forceinline__ void wgmma_fence() { asm volatile("wgmma.fence.sync.aligned;" ::: "memory"); }
__device__ __forceinline__ void wgmma_commit() { asm volatile("wgmma.commit_group.sync.aligned;" ::: "memory"); }
template <int N> __device__ __forceinline__ void wgmma_wait() { asm volatile("wgmma.wait_group.sync.aligned %0;" ::"n"(N) : "memory"); }
template <int SCALE_D>
__device__ __forceinline__ void wgmma_ss(float (&d)[112], uint32_t descA, uint32_t descB) {
    asm volatile(
        "{\n.reg .pred p;\n.reg .b64 da, db;\nsetp.ne.b32 p, %114, 0;\n"
        "mov.b64 da, {%112, 0x40000040};\nmov.b64 db, {%113, 0x10};\n"
        "wgmma.mma_async.sync.aligned.m64n224k16.f32.bf16.bf16 "
        "{%0, %1, %2, %3, %4, %5, %6, %7, %8, %9, %10, %11, %12, %13, %14, %15, "
        "%16, %17, %18, %19, %20, %21, %22, %23, %24, %25, %26, %27, %28, %29, %30, %31, "
        "%32, %33, %34, %35, %36, %37, %38, %39, %40, %41, %42, %43, %44, %45, %46, %47, "
        "%48, %49, %50, %51, %52, %53, %54, %55, %56, %57, %58, %59, %60, %61, %62, %63, "
        "%64, %65, %66, %67, %68, %69, %70, %71, %72, %73, %74, %75, %76, %77, %78, %79, "
        "%80, %81, %82, %83, %84, %85, %86, %87, %88, %89, %90, %91, %92, %93, %94, %95, "
        "%96, %97, %98, %99, %100, %101, %102, %103, %104, %105, %106, %107, %108, %109, %110, %111}, "
        "da, db, p, 1, 1, 0, 1;\n}\n"
        : "+f"(d[0]), "+f"(d[1]), "+f"(d[2]), "+f"(d[3]), "+f"(d[4]), "+f"(d[5]), "+f"(d[6]), "+f"(d[7]),
          "+f"(d[8]), "+f"(d[9]), "+f"(d[10]), "+f"(d[11]), "+f"(d[12]), "+f"(d[13]), "+f"(d[14]), "+f"(d[15]),
          "+f"(d[16]), "+f"(d[17]), "+f"(d[18]), "+f"(d[19]), "+f"(d[20]), "+f"(d[21]), "+f"(d[22]), "+f"(d[23]),
          "+f"(d[24]), "+f"(d[25]), "+f"(d[26]), "+f"(d[27]), "+f"(d[28]), "+f"(d[29]), "+f"(d[30]), "+f"(d[31]),
          "+f"(d[32]), "+f"(d[33]), "+f"(d[34]), "+f"(d[35]), "+f"(d[36]), "+f"(d[37]), "+f"(d[38]), "+f"(d[39]),
          "+f"(d[40]), "+f"(d[41]), "+f"(d[42]), "+f"(d[43]), "+f"(d[44]), "+f"(d[45]), "+f"(d[46]), "+f"(d[47]),
          "+f"(d[48]), "+f"(d[49]), "+f"(d[50]), "+f"(d[51]), "+f"(d[52]), "+f"(d[53]), "+f"(d[54]), "+f"(d[55]),
          "+f"(d[56]), "+f"(d[57]), "+f"(d[58]), "+f"(d[59]), "+f"(d[60]), "+f"(d[61]), "+f"(d[62]), "+f"(d[63]),
          "+f"(d[64]), "+f"(d[65]), "+f"(d[66]), "+f"(d[67]), "+f"(d[68]), "+f"(d[69]), "+f"(d[70]), "+f"(d[71]),
          "+f"(d[72]), "+f"(d[73]), "+f"(d[74]), "+f"(d[75]), "+f"(d[76]), "+f"(d[77]), "+f"(d[78]), "+f"(d[79]),
          "+f"(d[80]), "+f"(d[81]), "+f"(d[82]), "+f"(d[83]), "+f"(d[84]), "+f"(d[85]), "+f"(d[86]), "+f"(d[87]),
          "+f"(d[88]), "+f"(d[89]), "+f"(d[90]), "+f"(d[91]), "+f"(d[92]), "+f"(d[93]), "+f"(d[94]), "+f"(d[95]),
          "+f"(d[96]), "+f"(d[97]), "+f"(d[98]), "+f"(d[99]), "+f"(d[100]), "+f"(d[101]), "+f"(d[102]), "+f"(d[103]),
          "+f"(d[104]), "+f"(d[105]), "+f"(d[106]), "+f"(d[107]), "+f"(d[108]), "+f"(d[109]), "+f"(d[110]), "+f"(d[111])
        : "r"(descA), "r"(descB), "n"(SCALE_D));
}

template <int SCALE_D>
__device__ __forceinline__ void wgmma_ss(float (&d)[64], uint32_t descA, uint32_t descB) {
    asm volatile(
        "{\n.reg .pred p;\n.reg .b64 da, db;\nsetp.ne.b32 p, %66, 0;\n"
        "mov.b64 da, {%64, 0x40000040};\nmov.b64 db, {%65, 0x10};\n"
        "wgmma.mma_async.sync.aligned.m64n128k16.f32.bf16.bf16 "
        "{%0, %1, %2, %3, %4, %5, %6, %7, %8, %9, %10, %11, %12, %13, %14, %15, "
        "%16, %17, %18, %19, %20, %21, %22, %23, %24, %25, %26, %27, %28, %29, %30, %31, "
        "%32, %33, %34, %35, %36, %37, %38, %39, %40, %41, %42, %43, %44, %45, %46, %47, "
        "%48, %49, %50, %51, %52, %53, %54, %55, %56, %57, %58, %59, %60, %61, %62, %63}, "
        "da, db, p, 1, 1, 0, 1;\n}\n"
        : "+f"(d[0]), "+f"(d[1]), "+f"(d[2]), "+f"(d[3]), "+f"(d[4]), "+f"(d[5]), "+f"(d[6]), "+f"(d[7]),
          "+f"(d[8]), "+f"(d[9]), "+f"(d[10]), "+f"(d[11]), "+f"(d[12]), "+f"(d[13]), "+f"(d[14]), "+f"(d[15]),
          "+f"(d[16]), "+f"(d[17]), "+f"(d[18]), "+f"(d[19]), "+f"(d[20]), "+f"(d[21]), "+f"(d[22]), "+f"(d[23]),
          "+f"(d[24]), "+f"(d[25]), "+f"(d[26]), "+f"(d[27]), "+f"(d[28]), "+f"(d[29]), "+f"(d[30]), "+f"(d[31]),
          "+f"(d[32]), "+f"(d[33]), "+f"(d[34]), "+f"(d[35]), "+f"(d[36]), "+f"(d[37]), "+f"(d[38]), "+f"(d[39]),
          "+f"(d[40]), "+f"(d[41]), "+f"(d[42]), "+f"(d[43]), "+f"(d[44]), "+f"(d[45]), "+f"(d[46]), "+f"(d[47]),
          "+f"(d[48]), "+f"(d[49]), "+f"(d[50]), "+f"(d[51]), "+f"(d[52]), "+f"(d[53]), "+f"(d[54]), "+f"(d[55]),
          "+f"(d[56]), "+f"(d[57]), "+f"(d[58]), "+f"(d[59]), "+f"(d[60]), "+f"(d[61]), "+f"(d[62]), "+f"(d[63])
        : "r"(descA), "r"(descB), "n"(SCALE_D));
}

template <int SCALE_D>
__device__ __forceinline__ void wgmma_ss(float (&d)[32], uint32_t descA, uint32_t descB) {
    asm volatile(
        "{\n.reg .pred p;\n.reg .b64 da, db;\nsetp.ne.b32 p, %34, 0;\n"
        "mov.b64 da, {%32, 0x40000040};\nmov.b64 db, {%33, 0x10};\n"
        "wgmma.mma_async.sync.aligned.m64n64k16.f32.bf16.bf16 "
        "{%0, %1, %2, %3, %4, %5, %6, %7, %8, %9, %10, %11, %12, %13, %14, %15, "
        "%16, %17, %18, %19, %20, %21, %22, %23, %24, %25, %26, %27, %28, %29, %30, %31}, "
        "da, db, p, 1, 1, 0, 1;\n}\n"
        : "+f"(d[0]), "+f"(d[1]), "+f"(d[2]), "+f"(d[3]), "+f"(d[4]), "+f"(d[5]), "+f"(d[6]), "+f"(d[7]),
          "+f"(d[8]), "+f"(d[9]), "+f"(d[10]), "+f"(d[11]), "+f"(d[12]), "+f"(d[13]), "+f"(d[14]), "+f"(d[15]),
          "+f"(d[16]), "+f"(d[17]), "+f"(d[18]), "+f"(d[19]), "+f"(d[20]), "+f"(d[21]), "+f"(d[22]), "+f"(d[23]),
          "+f"(d[24]), "+f"(d[25]), "+f"(d[26]), "+f"(d[27]), "+f"(d[28]), "+f"(d[29]), "+f"(d[30]), "+f"(d[31])
        : "r"(descA), "r"(descB), "n"(SCALE_D));
}

template <int SCALE_D>
__device__ __forceinline__ void wgmma_ss(float (&d)[16], uint32_t descA, uint32_t descB) {
    asm volatile(
        "{\n.reg .pred p;\n.reg .b64 da, db;\nsetp.ne.b32 p, %18, 0;\n"
        "mov.b64 da, {%16, 0x40000040};\nmov.b64 db, {%17, 0x10};\n"
        "wgmma.mma_async.sync.aligned.m64n32k16.f32.bf16.bf16 "
        "{%0, %1, %2, %3, %4, %5, %6, %7, %8, %9, %10, %11, %12, %13, %14, %15}, "
        "da, db, p, 1, 1, 0, 1;\n}\n"
        : "+f"(d[0]), "+f"(d[1]), "+f"(d[2]), "+f"(d[3]), "+f"(d[4]), "+f"(d[5]), "+f"(d[6]), "+f"(d[7]),
          "+f"(d[8]), "+f"(d[9]), "+f"(d[10]), "+f"(d[11]), "+f"(d[12]), "+f"(d[13]), "+f"(d[14]), "+f"(d[15])
        : "r"(descA), "r"(descB), "n"(SCALE_D));
}

__device__ __forceinline__ void wgmma_rs(float (&d)[64], const uint4& a, uint32_t descB) {
    asm volatile(
        "{\n.reg .pred p;\n.reg .b64 db;\nsetp.eq.b32 p, 0, 0;\n"
        "mov.b64 db, {%68, 0x10};\n"
        "wgmma.mma_async.sync.aligned.m64n128k16.f32.bf16.bf16 "
        "{%0, %1, %2, %3, %4, %5, %6, %7, %8, %9, %10, %11, %12, %13, %14, %15, "
        "%16, %17, %18, %19, %20, %21, %22, %23, %24, %25, %26, %27, %28, %29, %30, %31, "
        "%32, %33, %34, %35, %36, %37, %38, %39, %40, %41, %42, %43, %44, %45, %46, %47, "
        "%48, %49, %50, %51, %52, %53, %54, %55, %56, %57, %58, %59, %60, %61, %62, %63}, "
        "{%64, %65, %66, %67}, db, p, 1, 1, 1;\n}\n"
        : "+f"(d[0]), "+f"(d[1]), "+f"(d[2]), "+f"(d[3]), "+f"(d[4]), "+f"(d[5]), "+f"(d[6]), "+f"(d[7]),
          "+f"(d[8]), "+f"(d[9]), "+f"(d[10]), "+f"(d[11]), "+f"(d[12]), "+f"(d[13]), "+f"(d[14]), "+f"(d[15]),
          "+f"(d[16]), "+f"(d[17]), "+f"(d[18]), "+f"(d[19]), "+f"(d[20]), "+f"(d[21]), "+f"(d[22]), "+f"(d[23]),
          "+f"(d[24]), "+f"(d[25]), "+f"(d[26]), "+f"(d[27]), "+f"(d[28]), "+f"(d[29]), "+f"(d[30]), "+f"(d[31]),
          "+f"(d[32]), "+f"(d[33]), "+f"(d[34]), "+f"(d[35]), "+f"(d[36]), "+f"(d[37]), "+f"(d[38]), "+f"(d[39]),
          "+f"(d[40]), "+f"(d[41]), "+f"(d[42]), "+f"(d[43]), "+f"(d[44]), "+f"(d[45]), "+f"(d[46]), "+f"(d[47]),
          "+f"(d[48]), "+f"(d[49]), "+f"(d[50]), "+f"(d[51]), "+f"(d[52]), "+f"(d[53]), "+f"(d[54]), "+f"(d[55]),
          "+f"(d[56]), "+f"(d[57]), "+f"(d[58]), "+f"(d[59]), "+f"(d[60]), "+f"(d[61]), "+f"(d[62]), "+f"(d[63])
        : "r"(a.x), "r"(a.y), "r"(a.z), "r"(a.w), "r"(descB));
}

__device__ __forceinline__ void wgmma_rs(float (&d)[32], const uint4& a, uint32_t descB) {
    asm volatile(
        "{\n.reg .pred p;\n.reg .b64 db;\nsetp.eq.b32 p, 0, 0;\n"
        "mov.b64 db, {%36, 0x10};\n"
        "wgmma.mma_async.sync.aligned.m64n64k16.f32.bf16.bf16 "
        "{%0, %1, %2, %3, %4, %5, %6, %7, %8, %9, %10, %11, %12, %13, %14, %15, "
        "%16, %17, %18, %19, %20, %21, %22, %23, %24, %25, %26, %27, %28, %29, %30, %31}, "
        "{%32, %33, %34, %35}, db, p, 1, 1, 1;\n}\n"
        : "+f"(d[0]), "+f"(d[1]), "+f"(d[2]), "+f"(d[3]), "+f"(d[4]), "+f"(d[5]), "+f"(d[6]), "+f"(d[7]),
          "+f"(d[8]), "+f"(d[9]), "+f"(d[10]), "+f"(d[11]), "+f"(d[12]), "+f"(d[13]), "+f"(d[14]), "+f"(d[15]),
          "+f"(d[16]), "+f"(d[17]), "+f"(d[18]), "+f"(d[19]), "+f"(d[20]), "+f"(d[21]), "+f"(d[22]), "+f"(d[23]),
          "+f"(d[24]), "+f"(d[25]), "+f"(d[26]), "+f"(d[27]), "+f"(d[28]), "+f"(d[29]), "+f"(d[30]), "+f"(d[31])
        : "r"(a.x), "r"(a.y), "r"(a.z), "r"(a.w), "r"(descB));
}

__device__ __forceinline__ void wgmma_rs(float (&d)[16], const uint4& a, uint32_t descB) {
    asm volatile(
        "{\n.reg .pred p;\n.reg .b64 db;\nsetp.eq.b32 p, 0, 0;\n"
        "mov.b64 db, {%20, 0x10};\n"
        "wgmma.mma_async.sync.aligned.m64n32k16.f32.bf16.bf16 "
        "{%0, %1, %2, %3, %4, %5, %6, %7, %8, %9, %10, %11, %12, %13, %14, %15}, "
        "{%16, %17, %18, %19}, db, p, 1, 1, 1;\n}\n"
        : "+f"(d[0]), "+f"(d[1]), "+f"(d[2]), "+f"(d[3]), "+f"(d[4]), "+f"(d[5]), "+f"(d[6]), "+f"(d[7]),
          "+f"(d[8]), "+f"(d[9]), "+f"(d[10]), "+f"(d[11]), "+f"(d[12]), "+f"(d[13]), "+f"(d[14]), "+f"(d[15])
        : "r"(a.x), "r"(a.y), "r"(a.z), "r"(a.w), "r"(descB));
}

constexpr int NT = N_ / BN, MT = M_ / BM;
constexpr int W_BYTES = BN * BK * 2;
constexpr int SLAB = 8 * BN * 4;
constexpr int SC_ROW = BN * 2;
constexpr int X_OFF = 0;
constexpr int W_OFF = 10 * 8192;
constexpr int R_OFF = W_OFF + 4 * W_BYTES;
constexpr int SC_OFF = R_OFF + W_BYTES - 2 * SC_ROW;
constexpr int RAW0_OFF = W_OFF + 2 * W_BYTES;
constexpr int SC0_OFF = W_OFF + 3 * W_BYTES;
constexpr int BAR_OFF = SC_OFF + 16 * SC_ROW;
constexpr int SMEM_BYTES = BAR_OFF + 896;
constexpr unsigned READY = MT * 7;
constexpr int UM = 22;
constexpr int NAG = 7;

__device__ __align__(1024) uint8_t g_wimg[(size_t)NT * KC * W_BYTES];
__device__ unsigned g_flag[NT * 32];

__host__ __device__ constexpr int slab_at(int u) { return u == 0 ? 2 : u == 1 ? 3 : u == 3 ? 4 : u == 5 ? 5 : (u >= 7 && u <= 16) ? u - 1 : -1; }
__host__ __device__ constexpr int wload_at(int u) {
    return u <= 10 ? ((u & 1) ? -1 : u / 2 + 1) : u <= 17 ? ((u & 1) ? (u + 3) / 2 : -1) : u == 18 ? 11 : u == 19 ? 12 : u == 20 ? 15 : u == 21 ? 13 : -1;
}
__host__ __device__ constexpr int tail_chunk(int j) { return j == 3 ? 15 : j == 4 ? 14 : 11 + j; }
__host__ __device__ constexpr int wbuf(int c) { return c == 15 ? 4 : c & 3; }

template <int NR>
__device__ __forceinline__ void store_cols(const float (&acc)[NR], uint8_t* p) {
#pragma unroll
    for (int j = 0; j < NR / 16; j++) {
        const int i = 16 * j;
        stg128(p + j * 64, pack_bf16(acc[i], acc[i + 1]), pack_bf16(acc[i + 4], acc[i + 5]), pack_bf16(acc[i + 8], acc[i + 9]), pack_bf16(acc[i + 12], acc[i + 13]));
        stg128(p + j * 64 + 8 * N_ * 2, pack_bf16(acc[i + 2], acc[i + 3]), pack_bf16(acc[i + 6], acc[i + 7]), pack_bf16(acc[i + 10], acc[i + 11]), pack_bf16(acc[i + 14], acc[i + 15]));
    }
}

__global__ void __cluster_dims__(2, 1, 1) __launch_bounds__(256, 1)
nf4_gemm_kernel(const uint8_t* __restrict__ qw, const __nv_bfloat16* __restrict__ cb, const __nv_bfloat16* __restrict__ absmax,
                uint8_t* __restrict__ wimg, unsigned* __restrict__ gflags, uint8_t* __restrict__ out, const unsigned zero,
                const __grid_constant__ CUtensorMap tmx, const __grid_constant__ CUtensorMap tmx64, const __grid_constant__ CUtensorMap tmq16,
                const __grid_constant__ CUtensorMap tmq8, const __grid_constant__ CUtensorMap tmq1, const __grid_constant__ CUtensorMap tms) {
    extern __shared__ __align__(1024) uint8_t smem[];
    const int rank = blockIdx.x & 1;
    const int mt = (blockIdx.x & 3) + (blockIdx.x >> 6) * 4, nt = (blockIdx.x >> 2) & 15;
    const uint8_t* share;
    asm volatile(
        "{\n.reg .b32 t, b, o, h;\n.reg .b64 a;\n.reg .pred p;\n"
        "mov.u32 t, %%tid.x;\nmov.u32 b, %%ctaid.x;\n"
        "shr.u32 h, t, 5;\nshl.b32 o, t, 5;\nmad.lo.u32 o, h, %2 - 1024, o;\n"
        "and.b32 h, b, 3;\nmad.lo.u32 o, h, 8 * %2 - %3 / 4, o;\n"
        "shr.u32 h, b, 6;\nmad.lo.u32 o, h, 32 * %2 - 16 * %3, o;\n"
        "mad.lo.u32 o, b, %3 / 4, o;\n"
        "cvt.u64.u32 a, o;\nadd.u64 a, a, %1;\n"
        "prefetch.global.L2 [a + 64 * %2];\n"
        "setp.lt.u32 p, b, 64;\n@p prefetch.global.L2 [a + 96 * %2];\n"
        "mov.b64 %0, a;\n}\n" : "=l"(share) : "l"(qw), "n"(N_ * 4), "n"(BN * 4));
    const uint32_t sbase = smem_u32(smem);
    const int warp = __shfl_sync(~0u, (int)(threadIdx.x >> 5), 0);
    const int wg = warp >> 2, wj = warp & 3;
    const int lane = threadIdx.x & 31;
    const uint32_t bars = sbase + BAR_OFF;
    const uint32_t snap = bars;
    const uint32_t xfull = bars + 64 + wg * 40;
    const uint32_t wfull = bars + 144;
    const uint32_t wempty = bars + 184;
    const uint32_t ringfull = bars + 216;
    const uint32_t rawbar = bars + 248;
    const uint32_t wown = bars + 264;
    const uint32_t stored = bars + 272 - 8;
    const uint32_t wlast = bars + 344;
    const uint32_t xbase = sbase + X_OFF + wg * 40960, wbase = sbase + W_OFF, rbase = sbase + R_OFF;
    const int xrow = mt * BM + wg * 128 + wj * 16;
    const uint8_t* wsrc = wimg + (size_t)nt * KC * W_BYTES;
    unsigned* flags = gflags + nt * 32;

    auto load_x = [&](int u, int cs = -1) {
        const int c = u < UM ? u >> 1 : tail_chunk((u - UM) % 5), b = u < UM ? u & 1 : (u - UM) / 5;
        mbar_expect_tx(xfull + 8 * (u % 5), cs >= 0 ? 3072 : 2048);
        tma_load_2d(xbase + (u % 5) * 8192 + wj * 2048, &tmx, c * BK, xrow + b * 64, xfull + 8 * (u % 5));
        if (cs >= 0) tma_load_2d(rbase + (cs & 3) * SLAB + warp * 1024, &tmq1, nt * BN + warp * 32, cs * BK + mt * 8, xfull + 8 * (u % 5));
    };
    auto load_x64 = [&](int g, int u) {
        const uint32_t bar = bars + 64 + g * 40 + 8 * u;
        mbar_arrive_n(bar, 3);
        mbar_expect_tx(bar, 8192);
        tma_load_2d(sbase + X_OFF + g * 40960 + u * 8192, &tmx64, (u >> 1) * BK, mt * BM + g * 128 + (u & 1) * 64, bar);
    };
    auto load_slab = [&](int c, uint32_t extra = 0) {
        mbar_expect_tx(ringfull + 8 * (c & 3), SLAB + extra);
        tma_load_3d(rbase + (c & 3) * SLAB, &tmq8, 0, c * BK + mt * 8, nt * 7, ringfull + 8 * (c & 3));
    };
    auto load_raw = [&](int p, uint32_t extra = 0) {
        mbar_expect_tx(rawbar + 8 * p, 2 * SLAB + extra);
        tma_load_3d(sbase + RAW0_OFF + p * 2 * SLAB, &tmq16, 0, rank * 32 + p * 16, nt * 7, rawbar + 8 * p);
    };
    if (warp == 7) {
        if (elect()) {
            mbar_init(ringfull + 8, 1); mbar_init(rawbar, 1); mbar_init(rawbar + 8, 1);
            load_slab(1, SC_ROW);
            bulk_load(sbase + SC0_OFF + SC_ROW, absmax + N_ + nt * BN, SC_ROW, ringfull + 8);
            load_raw(0, SC_ROW);
            bulk_load(sbase + SC0_OFF, absmax + nt * BN, SC_ROW, rawbar);
            load_raw(1);
            mbar_init(bars + 64, 4); mbar_init(bars + 72, 4); mbar_init(bars + 104, 4); mbar_init(bars + 112, 4); mbar_init(ringfull + 16, 1);
            mbar_init_fence();
        }
        __syncwarp();
    }
    uint4 c0, c1;
    asm volatile("ld.global.nc.v4.u32 {%0, %1, %2, %3}, [%8];\nld.global.nc.v4.u32 {%4, %5, %6, %7}, [%8 + 16];"
                 : "=r"(c0.x), "=r"(c0.y), "=r"(c0.z), "=r"(c0.w), "=r"(c1.x), "=r"(c1.y), "=r"(c1.z), "=r"(c1.w) : "l"(cb));
    if (warp < 7) delay(200);
    asm volatile("prefetch.global.L2 [%0];" ::"l"(share));
    if (blockIdx.x < 64) asm volatile("prefetch.global.L2 [%0];" ::"l"(share + 32 * N_ * 4));
    if (warp == 5 || warp == 6) {
        if (elect()) {
            if (warp == 6) {
#pragma unroll
                for (int s = 0; s < 5; s++) mbar_init(wfull + 8 * s, 1);
#pragma unroll
                for (int s = 0; s < 4; s++) mbar_init(wempty + 8 * s, 16);
                mbar_init(wown, 7); mbar_init(wlast, 1); mbar_init(ringfull, 1); mbar_init(ringfull + 24, 1);
                mbar_expect_tx(wfull, W_BYTES / 2);
            }
            if (warp == 5) {
#pragma unroll
                for (int s = 0; s < 10; s++) if (s % 5 >= 2) mbar_init(bars + 64 + 8 * s, 4);
#pragma unroll
                for (int s = 1; s <= NAG; s++) mbar_init(stored + 8 * s, s == 1 ? 7 : 224);
            }
            mbar_init_fence();
        }
        __syncwarp();
    }
    cluster_arrive();
    if (warp == 7) {
        if (elect()) { load_x64(0, 0); load_x64(0, 1); load_x64(1, 0); load_x64(1, 1); }
        __syncwarp();
    }
    const uint32_t rlane = (lane & 7) * 128 + ((((lane >> 3) * 2) ^ (lane & 7)) << 4);
    const uint32_t wlane = warp * 1024 + (lane & 7) * 16 + (lane >> 3) * 4;
    const uint32_t slabsrc = __shfl_sync(~0u, (warp < 7 ? warp * 1024 + rlane : 0) + sbase, lane);
    const uint32_t scsrc = __shfl_sync(~0u, sbase + (warp < 7 ? warp * 64 : 0) + (lane >> 3) * 16, lane);
    uint8_t* const gdst = wimg + (size_t)nt * KC * W_BYTES + (mt >> 1) * SLAB + (mt & 1) * 128 + wlane;
    uint8_t* const gkeep = (uint8_t*)__shfl_sync(~0u, (unsigned long long)gdst, lane);
    uint8_t* const gread = (uint8_t*)__shfl_sync(~0u, (unsigned long long)(warp < 7 ? gdst + (lane >> 3) * 252 : (uint8_t*)flags + (lane >> 3) * 16), lane);
    Lut lut = {};
    if (warp < 7) {
        lut.lo[0] = __byte_perm(c0.x, c0.y, 0x6420); lut.hi[0] = __byte_perm(c0.x, c0.y, 0x7531);
        lut.lo[1] = __byte_perm(c0.z, c0.w, 0x6420); lut.hi[1] = __byte_perm(c0.z, c0.w, 0x7531);
        lut.lo[2] = __byte_perm(c1.x, c1.y, 0x6420); lut.hi[2] = __byte_perm(c1.x, c1.y, 0x7531);
        lut.lo[3] = __byte_perm(c1.z, c1.w, 0x6420); lut.hi[3] = __byte_perm(c1.z, c1.w, 0x7531);
    }
    cluster_wait();

    auto store_slab = [&](int c, uint32_t p, const uint4& sc) {
        const uint4 w = dequant8(p, sc, lut);
        uint8_t* g = gkeep + (size_t)c * W_BYTES;
        stg32(g, w.x); stg32(g + 256, w.y); stg32(g + 512, w.z); stg32(g + 768, w.w);
        if (c == 1) {
            __syncwarp();
            if (elect()) mbar_arrive(stored + 8);
            __syncwarp();
        } else {
            read_l2(scsrc + SC_OFF + SC_ROW * c, gread + (size_t)c * W_BYTES, (lane & 7) == 0);
            if (c <= NAG) read_arrive(stored + 8 * c);
        }
    };
    auto take_sample = [&]() { read_l2(scsrc + BAR_OFF, gread, (lane & 7) == 0); };
    auto load_w = [&](int c) {
        read_wait<0>();
        poll_ge(flags + c, lds32(snap + 4 * c), READY);
        asm volatile("fence.acquire.gpu;" ::: "memory");
        asm volatile("fence.proxy.async.global;" ::: "memory");
        if (c >= 4 && c < 15) mbar_wait(wempty + 8 * (c & 3), ((c >> 2) - 1) & 1);
        if (elect()) {
            if (c == 1) {
                mbar_expect_tx(wfull + 8, W_BYTES / 2);
                bulk_load_mc(wbase + W_BYTES + rank * SLAB, wsrc + W_BYTES + rank * SLAB, SLAB, wfull + 8);
                mbar_expect_tx(wlast, W_BYTES / 2);
                bulk_load_mc(wbase + W_BYTES + (2 + rank) * SLAB, wsrc + W_BYTES + (2 + rank) * SLAB, SLAB, wlast);
            } else {
                mbar_expect_tx(wfull + 8 * wbuf(c), W_BYTES);
                bulk_load_mc(wbase + wbuf(c) * W_BYTES + rank * (W_BYTES / 2), wsrc + (size_t)c * W_BYTES + rank * (W_BYTES / 2), W_BYTES / 2, wfull + 8 * wbuf(c));
            }
        }
        __syncwarp();
    };

    if (warp < 7) {
        mbar_wait(ringfull + 8, 0);
        store_slab(1, pack8(lds128(slabsrc + R_OFF + SLAB), lds128((slabsrc ^ 16) + R_OFF + SLAB)), lds128(scsrc + SC0_OFF + SC_ROW));
        const uint32_t tab = prmt(prmt(lane & 8 ? lut.lo[2] : lut.lo[0], lane & 8 ? lut.lo[3] : lut.lo[1], lane & 7),
                                  prmt(lane & 8 ? lut.hi[2] : lut.hi[0], lane & 8 ? lut.hi[3] : lut.hi[1], lane & 7), 0x40);
        uint4 sc;
#pragma unroll
        for (int p = 0; p < 2; p++) {
            mbar_wait(rawbar + 8 * p, 0);
            if (p == 0) { sc = lds128(scsrc + SC0_OFF); }
            const uint32_t a = sbase + RAW0_OFF + p * 2 * SLAB + warp * 2048;
            const uint4 v0 = lds128(a + rlane), v1 = lds128(a + (rlane ^ 16)), v2 = lds128(a + rlane + 1024), v3 = lds128(a + (rlane ^ 16) + 1024);
            const uint4 w0 = dequant8(pack8(v0, v1), sc, lut), w1 = dequant8_shfl(v2, v3, sc, tab);
            const uint32_t d = wbase + (2 * rank + p) * SLAB, e = d + wlane;
            sts32(e, w0.x); sts32(e + 256, w0.y); sts32(e + 512, w0.z); sts32(e + 768, w0.w);
            sts32(e + 128, w1.x); sts32(e + 384, w1.y); sts32(e + 640, w1.z); sts32(e + 896, w1.w);
            fence_async_smem();
            __syncwarp();
            if (elect()) {
                if (p == 1) mbar_arrive(wown);
                copy_to_peer(d + warp * 1024, 1024, wfull, rank ^ 1);
            }
            __syncwarp();
        }
    } else {
        mbar_wait(stored + 8, 0);
        const unsigned v = ld_relaxed(wsrc + W_BYTES + (mt >> 1) * SLAB + (mt & 1) * 128 + (lane < 28 ? lane : 0) * 256);
        if (elect()) {
            load_slab(2, 14 * SC_ROW);
            tma_load_2d(sbase + SC_OFF + 2 * SC_ROW, &tms, nt * BN, 2, ringfull + 16);
        }
        __syncwarp();
        const unsigned n = after(7, v, zero);
        __syncwarp();
        if (elect()) red_add(flags + 1, n);
        __syncwarp();
        if (elect()) { load_x64(0, 2); load_x64(1, 2); load_x64(0, 3); load_x64(1, 3); load_slab(3); }
        __syncwarp();
    }

    float acc0[112], acc1[112];
    const uint32_t descA = ((xbase & 0x3FFFF) >> 4) | (1u << 16), descB = ((wbase & 0x3FFFF) >> 4) | ((128u >> 4) << 16);
    static_for<0, UM>([&](auto U) __attribute__((always_inline)) {
        constexpr int u = U.value, kc = u >> 1;
        constexpr int c = slab_at(u);
        uint32_t da = descA, db = descB;
        asm volatile("" : "+r"(da), "+r"(db));
        uint4 q0, q1, sc;
        auto slab_loads = [&]() {
            q0 = lds128(slabsrc + R_OFF + (c & 3) * SLAB); q1 = lds128((slabsrc ^ 16) + R_OFF + (c & 3) * SLAB);
            sc = lds128(scsrc + SC_OFF + SC_ROW * c);
        };
        if (u < 4) {
            if (u == 0) mbar_wait3(xfull, 0, xfull + 8, 0, wown, 0);
            if (u == 1) mbar_wait(wfull, 0);
            if (u == 2) mbar_wait3(xfull + 16, 0, xfull + 24, 0, wfull + 8, 0);
            if (u == 3) { mbar_wait2(wlast, 0, ringfull, 0); slab_loads(); }
            if (u == 0 && warp == 7) take_sample();
            const int h = u < 2 ? rank ^ u : u & 1;
            da += kc * 1024 + h * 4; db += kc * (W_BYTES >> 4) + h * (2 * SLAB >> 4);
            wgmma_fence();
            wgmma_ss<u != 0>(acc0, da, db); wgmma_ss<u != 0>(acc1, da + 512, db);
            wgmma_ss<1>(acc0, da + 2, db + (SLAB >> 4)); wgmma_ss<1>(acc1, da + 514, db + (SLAB >> 4));
        } else {
            if (u & 1) mbar_wait(xfull + 8 * (u % 5), (u / 5) & 1);
            else mbar_wait2(xfull + 8 * (u % 5), (u / 5) & 1, wfull + 8 * (kc & 3), (kc >> 2) & 1);
            if (c >= 0) slab_loads();
            da += (u % 5) * 512; db += (kc & 3) * (W_BYTES >> 4);
            wgmma_fence();
#pragma unroll
            for (int ks = 0; ks < 4; ks++) {
                if (u & 1) wgmma_ss<1>(acc1, da + ks * 2, db + ks * (SLAB >> 4));
                else wgmma_ss<1>(acc0, da + ks * 2, db + ks * (SLAB >> 4));
            }
        }
        wgmma_commit();
        if (u >= 2) wgmma_wait<1>();
        if (warp < 7) {
            constexpr int cp = slab_at(u - 2) > NAG ? slab_at(u - 2) : -1;
            if (u < 2) { mbar_wait(ringfull + 8 * c, 0); slab_loads(); }
            uint32_t p = 0;
            if (c >= 0) p = pack8(q0, q1);
            if (cp >= 0) { if (slab_at(u - 1) >= 0) read_wait<1>(); else read_wait<0>(); }
            if (u >= 2) {
                if (elect()) {
                    if (u <= 17) load_x(u + 3, slab_at(u + 3));
                    if (u >= 17) load_x(u + 4);
                    if (!(u & 1)) mbar_arrive_both(wempty + 8 * ((kc - 1) & 3));
                    if (cp >= 0) red_add(flags + cp, 1);
                }
                __syncwarp();
            }
            if (c >= 0) store_slab(c, p, sc);
        } else {
            constexpr int cw = wload_at(u), cc = slab_at(u - 1) <= NAG ? slab_at(u - 1) : -1;
            if (cw >= 0 && cw <= 6) load_w(cw);
            if (u != 1) {
                if (elect()) {
                    if (u == 0) load_slab(4);
                    if (u >= 2 && u <= 17) load_x(u + 3);
                    if (u >= 17) load_x(u + 4);
                    if (u >= 2 && !(u & 1)) mbar_arrive_both(wempty + 8 * ((kc - 1) & 3));
                }
                __syncwarp();
            }
            if (cc >= 0) {
                mbar_wait(stored + 8 * cc, 0);
                if (elect()) red_add(flags + cc, 7);
                __syncwarp();
            }
            if (u == 1) {
                if (elect()) { load_x64(0, 4); load_x64(1, 4); }
                __syncwarp();
                delay(300);
            }
            if (cw > 6) load_w(cw);
            if (wload_at(u + 1) >= 0) take_sample();
        }
    });

    uint32_t tA = descA, tB = descB;
    asm volatile("" : "+r"(tA), "+r"(tB));
    if (wg == 1) {
        wgmma_wait<0>();
        if (elect()) { load_x(UM + 4); mbar_arrive_both(wempty + 16); }
        __syncwarp();
        if (warp == 7) load_w(14);
        if (warp == 7 && lane == 0) {
            if (atomicAdd(flags + 16, 1) == MT - 1) {
#pragma unroll
                for (int c = 0; c <= 16; c++) flags[c] = 0;
            }
        }
        __syncwarp();
        bar_sync<256>(1);
    }
#pragma unroll
    for (int j = 0; j < 5; j++) {
        const int c = tail_chunk(j), v = UM + j;
        mbar_wait2(xfull + 8 * (v % 5), (v / 5) & 1, wfull + 8 * wbuf(c), c == 15 ? 0 : (c >> 2) & 1);
        wgmma_fence();
#pragma unroll
        for (int ks = 0; ks < 4; ks++) wgmma_ss<1>(acc0, tA + (v % 5) * 512 + ks * 2, tB + wbuf(c) * (W_BYTES >> 4) + ks * (SLAB >> 4));
        wgmma_commit();
        if (j == 4) bar_arrive<256>(1 + wg);
        if (j == 0) {
            if (wg == 0) {
                wgmma_wait<1>();
                if (elect()) { load_x(UM + 4); mbar_arrive_both(wempty + 16); }
                __syncwarp();
            }
        } else if (j >= 2) {
            wgmma_wait<2>();
            if (elect()) load_x(v + 3);
            __syncwarp();
        }
    }
    wgmma_wait<1>();
    if (elect()) load_x(UM + 8);
    __syncwarp();
    wgmma_wait<0>();
    if (elect()) load_x(UM + 9);
    __syncwarp();
    uint8_t* optr = out + (size_t)(xrow + (lane >> 2)) * (N_ * 2) + nt * (BN * 2) + (lane & 3) * 16;
    float pa[64], pb[32], pc[16];
#pragma unroll
    for (int i = 0; i < 64; i++) asm volatile("mov.b32 %0, %1;" : "=f"(pa[i]) : "f"(acc1[i]));
#pragma unroll
    for (int i = 0; i < 32; i++) asm volatile("mov.b32 %0, %1;" : "=f"(pb[i]) : "f"(acc1[64 + i]));
#pragma unroll
    for (int i = 0; i < 16; i++) asm volatile("mov.b32 %0, %1;" : "=f"(pc[i]) : "f"(acc1[96 + i]));
    uint4 af[20];
    uint32_t pk[56];
    auto store_pk = [&](int h0, int h1) {
#pragma unroll
        for (int h = h0; h < h1; h++) {
            const int i = 8 * (h >> 1) + (h & 1);
            stg128(optr + (h >> 1) * 64 + (h & 1) * (8 * N_ * 2), pk[i], pk[i + 2], pk[i + 4], pk[i + 6]);
        }
    };
    const uint32_t alane = xbase + wj * 2048 + (lane & 15) * 128 + (((lane >> 4) ^ (lane & 7)) << 4);
    static_for<0, 4>([&](auto J) __attribute__((always_inline)) {
        constexpr int j = J.value, v = UM + 5 + j;
        mbar_wait(xfull + 8 * (v % 5), (v / 5) & 1);
#pragma unroll
        for (int ks = 0; ks < 4; ks++) af[4 * j + ks] = ldmatrix_x4((alane ^ (ks * 32)) + (v % 5) * 8192);
#pragma unroll
        for (int i = 16 * j; i < (j < 3 ? 16 * j + 16 : 56); i++) pk[i] = pack_bf16(acc0[2 * i], acc0[2 * i + 1]);
        store_pk(2 * j, 2 * j + 2);
    });
    store_pk(8, 10);
    if (wg == 0) store_pk(10, 14);
    auto piece = [&](auto& d, int cb) {
        wgmma_fence();
#pragma unroll
        for (int j = 0; j < 5; j++) {
            if (cb == 0 && j == 4) { mbar_wait(xfull + 8 * ((UM + 9) % 5), ((UM + 9) / 5) & 1); wgmma_fence(); }
#pragma unroll
            for (int ks = 0; ks < 4; ks++) {
                const uint32_t db = tB + wbuf(tail_chunk(j)) * (W_BYTES >> 4) + ks * (SLAB >> 4) + cb * 64;
                if (j < 4 || cb > 0) wgmma_rs(d, af[4 * j + ks], db);
                else wgmma_ss<1>(d, tA + ((UM + 9) % 5) * 512 + ks * 2, db);
            }
        }
        wgmma_commit();
    };
    bar_sync<256>(2 + wg);
    piece(pa, 0);
    bar_arrive<256>(3 + wg);
    if (wg == 1) store_pk(10, 14);
    wgmma_wait<0>();
#pragma unroll
    for (int ks = 0; ks < 4; ks++) af[16 + ks] = ldmatrix_x4((alane ^ (ks * 32)) + ((UM + 9) % 5) * 8192);
    optr += 64 * N_ * 2;
    store_cols(pa, optr);
    bar_sync<256>(4 + wg);
    piece(pb, 4);
    bar_arrive<256>(5 + wg);
    wgmma_wait<0>();
    store_cols(pb, optr + 4 * 64);
    bar_sync<256>(6 + wg);
    piece(pc, 6);
    if (wg == 0) bar_arrive<256>(7);
    cluster_arrive();
    wgmma_wait<0>();
    store_cols(pc, optr + 6 * 64);
    cluster_wait();
}

typedef CUresult (*EncodeFn)(CUtensorMap*, CUtensorMapDataType, cuuint32_t, void*, const cuuint64_t*, const cuuint64_t*,
                             const cuuint32_t*, const cuuint32_t*, CUtensorMapInterleave, CUtensorMapSwizzle,
                             CUtensorMapL2promotion, CUtensorMapFloatOOBfill);

extern "C" void kernel_launch(void* const* d_in, const int* in_sizes, int n_in, void* d_out, int out_size) {
    static EncodeFn encode = nullptr;
    static void *wimg = nullptr, *gflags = nullptr;
    if (!encode) {
        cudaGetSymbolAddress(&wimg, g_wimg);
        cudaGetSymbolAddress(&gflags, g_flag);
        void* fn = nullptr;
        cudaDriverEntryPointQueryResult qr;
        cudaGetDriverEntryPoint("cuTensorMapEncodeTiled", &fn, cudaEnableDefault, &qr);
        encode = (EncodeFn)fn;
        cudaFuncSetAttribute(nf4_gemm_kernel, cudaFuncAttributeMaxDynamicSharedMemorySize, SMEM_BYTES);
    }
    void *x = d_in[0], *qw = d_in[1], *cb = d_in[2], *absmax = d_in[3];
    auto map = [&](CUtensorMapDataType t, int rank, void* p, const cuuint64_t* dims, const cuuint64_t* strides, const cuuint32_t* box, bool swizzle) {
        CUtensorMap m;
        const cuuint32_t es[3] = {1, 1, 1};
        encode(&m, t, rank, p, dims, strides, box, es, CU_TENSOR_MAP_INTERLEAVE_NONE,
               swizzle ? CU_TENSOR_MAP_SWIZZLE_128B : CU_TENSOR_MAP_SWIZZLE_NONE,
               swizzle ? CU_TENSOR_MAP_L2_PROMOTION_L2_128B : CU_TENSOR_MAP_L2_PROMOTION_NONE, CU_TENSOR_MAP_FLOAT_OOB_FILL_NONE);
        return m;
    };
    const cuuint64_t xd[2] = {K_, M_}, xs[1] = {K_ * 2};
    const cuuint64_t q3d[3] = {32, K_, N_ / 32}, q3s[2] = {N_ * 4, 128};
    const cuuint64_t q2d[2] = {N_, K_}, q2s[1] = {N_ * 4};
    const cuuint64_t sd[2] = {N_, KC}, ss[1] = {N_ * 2};
    const cuuint32_t bx[2] = {BK, 16}, bx64[2] = {BK, 64}, bq16[3] = {32, 16, 7}, bq8[3] = {32, 8, 7}, bq1[2] = {32, 8}, bs[2] = {BN, KC - 2};
    nf4_gemm_kernel<<<128, 256, SMEM_BYTES>>>(
        (const uint8_t*)qw, (const __nv_bfloat16*)cb, (const __nv_bfloat16*)absmax, (uint8_t*)wimg, (unsigned*)gflags, (uint8_t*)d_out, 0u,
        map(CU_TENSOR_MAP_DATA_TYPE_BFLOAT16, 2, x, xd, xs, bx, true), map(CU_TENSOR_MAP_DATA_TYPE_BFLOAT16, 2, x, xd, xs, bx64, true),
        map(CU_TENSOR_MAP_DATA_TYPE_INT32, 3, qw, q3d, q3s, bq16, true), map(CU_TENSOR_MAP_DATA_TYPE_INT32, 3, qw, q3d, q3s, bq8, true),
        map(CU_TENSOR_MAP_DATA_TYPE_INT32, 2, qw, q2d, q2s, bq1, true), map(CU_TENSOR_MAP_DATA_TYPE_BFLOAT16, 2, absmax, sd, ss, bs, false));
}
```

```cpp
#include <cuda_runtime.h>
#include <cuda_bf16.h>
#include <cuda.h>
#include <stdint.h>

constexpr int M_ = 2048, K_ = 1024, N_ = 3584;
constexpr int BM = 256, BN = 224, BK = 64;
constexpr int KC = K_ / BK;

__device__ __forceinline__ uint32_t smem_u32(const void* p) { return (uint32_t)__cvta_generic_to_shared(p); }
__device__ __forceinline__ bool elect() {
    uint32_t ok;
    asm volatile("{\n.reg .pred p;\nelect.sync _|p, 0xffffffff;\nselp.u32 %0, 1, 0, p;\n}\n" : "=r"(ok));
    return ok != 0;
}
template <int I> struct IC { static constexpr int value = I; };
template <int I, int N, class F> __device__ __forceinline__ void static_for(F&& f) {
    if constexpr (I < N) { f(IC<I>{}); static_for<I + 1, N>(f); }
}

__device__ __forceinline__ void mbar_init(uint32_t bar, uint32_t cnt) { asm volatile("mbarrier.init.shared::cta.b64 [%0], %1;" ::"r"(bar), "r"(cnt) : "memory"); }
__device__ __forceinline__ void mbar_init_fence() { asm volatile("fence.mbarrier_init.release.cluster;" ::: "memory"); }
__device__ __forceinline__ void mbar_expect_tx(uint32_t bar, uint32_t bytes) { asm volatile("mbarrier.arrive.expect_tx.shared::cta.b64 _, [%0], %1;" ::"r"(bar), "r"(bytes) : "memory"); }
__device__ __forceinline__ void mbar_arrive(uint32_t bar) { asm volatile("mbarrier.arrive.shared::cta.b64 _, [%0];" ::"r"(bar) : "memory"); }
__device__ __forceinline__ void mbar_arrive_n(uint32_t bar, uint32_t n) { asm volatile("mbarrier.arrive.shared::cta.b64 _, [%0], %1;" ::"r"(bar), "r"(n) : "memory"); }
__device__ __forceinline__ void mbar_arrive_both(uint32_t bar) {
    asm volatile("{\n.reg .b32 ra;\nmapa.shared::cluster.u32 ra, %0, 0;\nmbarrier.arrive.shared::cluster.b64 _, [ra];\n"
                 "mapa.shared::cluster.u32 ra, %0, 1;\nmbarrier.arrive.shared::cluster.b64 _, [ra];\n}\n" ::"r"(bar) : "memory");
}
#define MBAR_TRY(p, b, q) "mbarrier.try_wait.parity.shared::cta.b64 " p ", [" b "], " q ";\n"
#define MBAR_WAIT(TRY) \
    "{\n.reg .pred p0, p1, p2;\n.reg .b32 n;\n" TRY "@p0 bra LAB_DONE;\nmov.b32 n, 0;\nLAB_WAIT:\n" TRY \
    "@p0 bra LAB_DONE;\nadd.u32 n, n, 1;\nsetp.lt.u32 p0, n, 0x40000;\n@p0 bra LAB_WAIT;\ntrap;\nLAB_DONE:\n}\n"
__device__ __forceinline__ void mbar_wait(uint32_t b0, uint32_t q0) {
    asm volatile(MBAR_WAIT(MBAR_TRY("p0", "%0", "%1")) ::"r"(b0), "r"(q0) : "memory");
}
__device__ __forceinline__ void mbar_wait2(uint32_t b0, uint32_t q0, uint32_t b1, uint32_t q1) {
    asm volatile(MBAR_WAIT(MBAR_TRY("p0", "%0", "%1") MBAR_TRY("p1", "%2", "%3") "and.pred p0, p0, p1;\n")
                 ::"r"(b0), "r"(q0), "r"(b1), "r"(q1) : "memory");
}
__device__ __forceinline__ void mbar_wait3(uint32_t b0, uint32_t q0, uint32_t b1, uint32_t q1, uint32_t b2, uint32_t q2) {
    asm volatile(MBAR_WAIT(MBAR_TRY("p0", "%0", "%1") MBAR_TRY("p1", "%2", "%3") MBAR_TRY("p2", "%4", "%5") "and.pred p0, p0, p1;\nand.pred p0, p0, p2;\n")
                 ::"r"(b0), "r"(q0), "r"(b1), "r"(q1), "r"(b2), "r"(q2) : "memory");
}
__device__ __forceinline__ void cluster_arrive() { asm volatile("barrier.cluster.arrive.relaxed.aligned;" ::: "memory"); }
__device__ __forceinline__ void cluster_wait() { asm volatile("barrier.cluster.wait.acquire.aligned;" ::: "memory"); }
template <int NTHR> __device__ __forceinline__ void bar_arrive(int id) { asm volatile("bar.arrive %0, %1;" ::"r"(id), "n"(NTHR) : "memory"); }
template <int NTHR> __device__ __forceinline__ void bar_sync(int id) { asm volatile("bar.sync %0, %1;" ::"r"(id), "n"(NTHR) : "memory"); }
__device__ __forceinline__ void delay(unsigned clks) {
    asm volatile(
        "{\n.reg .pred p;\n.reg .b32 t0, t;\n"
        "mov.u32 t0, %%clock;\n"
        "LAB_DELAY:\n"
        "mov.u32 t, %%clock;\n"
        "sub.u32 t, t, t0;\n"
        "setp.lt.u32 p, t, %0;\n"
        "vote.sync.any.pred p, p, 0xffffffff;\n"
        "@p bra.uni LAB_DELAY;\n}\n" ::"r"(clks) : "memory");
}

__device__ __forceinline__ void tma_load_2d(uint32_t dst, const CUtensorMap* tm, int c0, int c1, uint32_t bar) {
    asm volatile("cp.async.bulk.tensor.2d.shared::cluster.global.mbarrier::complete_tx::bytes [%0], [%1, {%2, %3}], [%4];"
                 ::"r"(dst), "l"(tm), "r"(c0), "r"(c1), "r"(bar) : "memory");
}
__device__ __forceinline__ void tma_load_3d(uint32_t dst, const CUtensorMap* tm, int c0, int c1, int c2, uint32_t bar) {
    asm volatile("cp.async.bulk.tensor.3d.shared::cluster.global.mbarrier::complete_tx::bytes [%0], [%1, {%2, %3, %4}], [%5];"
                 ::"r"(dst), "l"(tm), "r"(c0), "r"(c1), "r"(c2), "r"(bar) : "memory");
}
__device__ __forceinline__ void bulk_load(uint32_t dst, const void* src, uint32_t bytes, uint32_t bar) {
    asm volatile("cp.async.bulk.shared::cluster.global.mbarrier::complete_tx::bytes [%0], [%1], %2, [%3];"
                 ::"r"(dst), "l"(src), "r"(bytes), "r"(bar) : "memory");
}
__device__ __forceinline__ void bulk_load_mc(uint32_t dst, const void* src, uint32_t bytes, uint32_t bar) {
    asm volatile("cp.async.bulk.shared::cluster.global.mbarrier::complete_tx::bytes.multicast::cluster [%0], [%1], %2, [%3], %4;"
                 ::"r"(dst), "l"(src), "r"(bytes), "r"(bar), "h"((uint16_t)3) : "memory");
}
__device__ __forceinline__ uint32_t mapa(uint32_t addr, uint32_t cta) {
    uint32_t r; asm("mapa.shared::cluster.u32 %0, %1, %2;" : "=r"(r) : "r"(addr), "r"(cta)); return r;
}
__device__ __forceinline__ void copy_to_peer(uint32_t addr, uint32_t bytes, uint32_t bar, uint32_t peer) {
    asm volatile("cp.async.bulk.shared::cluster.shared::cta.mbarrier::complete_tx::bytes [%0], [%1], %2, [%3];"
                 ::"r"(mapa(addr, peer)), "r"(addr), "r"(bytes), "r"(mapa(bar, peer)) : "memory");
}
__device__ __forceinline__ void fence_async_smem() { asm volatile("fence.proxy.async.shared::cta;" ::: "memory"); }

__device__ __forceinline__ uint4 lds128(uint32_t a) {
    uint4 v; asm volatile("ld.shared.v4.b32 {%0, %1, %2, %3}, [%4];" : "=r"(v.x), "=r"(v.y), "=r"(v.z), "=r"(v.w) : "r"(a) : "memory"); return v;
}
__device__ __forceinline__ uint32_t lds32(uint32_t a) {
    uint32_t v; asm volatile("ld.shared.b32 %0, [%1];" : "=r"(v) : "r"(a) : "memory"); return v;
}
__device__ __forceinline__ uint4 ldmatrix_x4(uint32_t a) {
    uint4 v;
    asm volatile("ldmatrix.sync.aligned.m8n8.x4.shared.b16 {%0, %1, %2, %3}, [%4];" : "=r"(v.x), "=r"(v.y), "=r"(v.z), "=r"(v.w) : "r"(a) : "memory");
    return v;
}
__device__ __forceinline__ void sts32(uint32_t a, uint32_t v) { asm volatile("st.shared.b32 [%0], %1;" ::"r"(a), "r"(v) : "memory"); }
__device__ __forceinline__ void stg32(void* p, uint32_t v) { asm volatile("st.global.b32 [%0], %1;" ::"l"(p), "r"(v) : "memory"); }
__device__ __forceinline__ void stg128(void* p, uint32_t a, uint32_t b, uint32_t c, uint32_t d) {
    asm volatile("st.global.v4.b32 [%0], {%1, %2, %3, %4};" ::"l"(p), "r"(a), "r"(b), "r"(c), "r"(d) : "memory");
}

__device__ __forceinline__ unsigned ld_relaxed(const void* p) {
    unsigned v; asm volatile("ld.relaxed.gpu.global.u32 %0, [%1];" : "=r"(v) : "l"(p) : "memory"); return v;
}
__device__ __forceinline__ void read_l2(uint32_t dst, const void* src, uint32_t on) {
    asm volatile("{\n.reg .pred p;\nsetp.ne.u32 p, %2, 0;\n@p cp.async.cg.shared.global [%0], [%1], 16;\n}\ncp.async.commit_group;" ::"r"(dst), "l"(src), "r"(on) : "memory");
}
template <int N> __device__ __forceinline__ void read_wait() { asm volatile("cp.async.wait_group %0;" ::"n"(N) : "memory"); __syncwarp(); }
__device__ __forceinline__ void read_arrive(uint32_t bar) { asm volatile("cp.async.mbarrier.arrive.noinc.shared::cta.b64 [%0];" ::"r"(bar) : "memory"); }
__device__ __forceinline__ unsigned after(unsigned n, unsigned p, unsigned z) {
    unsigned r; asm volatile("lop3.b32 %0, %1, %2, %3, 0xea;" : "=r"(r) : "r"(p), "r"(z), "r"(n)); return r;
}
__device__ __forceinline__ void red_add(unsigned* f, unsigned n) { asm volatile("red.relaxed.gpu.global.add.u32 [%0], %1;" ::"l"(f), "r"(n) : "memory"); }
__device__ __forceinline__ void poll_ge(const unsigned* f, unsigned v, unsigned ready) {
    asm volatile(
        "{\n.reg .pred p;\n.reg .b32 v, n;\n"
        "setp.lt.u32 p, %1, %2;\n"
        "vote.sync.any.pred p, p, 0xffffffff;\n"
        "@!p bra.uni LAB_DONE;\n"
        "mov.b32 n, 0;\n"
        "LAB_POLL:\n"
        "ld.relaxed.gpu.global.u32 v, [%0];\n"
        "setp.lt.u32 p, v, %2;\n"
        "vote.sync.any.pred p, p, 0xffffffff;\n"
        "@!p bra.uni LAB_DONE;\n"
        "add.u32 n, n, 1;\n"
        "setp.lt.u32 p, n, 0x400000;\n"
        "@p bra.uni LAB_POLL;\n"
        "LAB_DONE:\n}\n" ::"l"(f), "r"(v), "r"(ready) : "memory");
}

__device__ __forceinline__ uint32_t pack_bf16(float lo, float hi) {
    uint32_t r; asm("cvt.rn.bf16x2.f32 %0, %1, %2;" : "=r"(r) : "f"(hi), "f"(lo)); return r;
}
__device__ __forceinline__ uint32_t mul_bf16x2(uint32_t a, uint32_t b) { uint32_t r; asm("mul.rn.bf16x2 %0, %1, %2;" : "=r"(r) : "r"(a), "r"(b)); return r; }
__device__ __forceinline__ uint32_t prmt(uint32_t a, uint32_t b, uint32_t s) { uint32_t r; asm("prmt.b32 %0, %1, %2, %3;" : "=r"(r) : "r"(a), "r"(b), "r"(s)); return r; }
__device__ __forceinline__ uint32_t madi(uint32_t hi, uint32_t m, uint32_t lo) { uint32_t r; asm("mad.lo.u32 %0, %1, %2, %3;" : "=r"(r) : "r"(hi), "r"(m), "r"(lo)); return r; }
__device__ __forceinline__ uint32_t pack8(const uint4& a, const uint4& b) {
    return madi(madi(madi(b.w, 65536, a.w), 16, madi(b.z, 65536, a.z)), 256, madi(madi(b.y, 65536, a.y), 16, madi(b.x, 65536, a.x)));
}
struct Lut { uint32_t lo[4], hi[4]; };
__device__ __forceinline__ void lookup4(uint32_t s7, uint32_t sel, const Lut& t, uint32_t& w01, uint32_t& w23) {
    const uint32_t lo = prmt(prmt(t.lo[0], t.lo[1], s7), prmt(t.lo[2], t.lo[3], s7), sel);
    const uint32_t hi = prmt(prmt(t.hi[0], t.hi[1], s7), prmt(t.hi[2], t.hi[3], s7), sel);
    w01 = prmt(lo, hi, 0x5140);
    w23 = prmt(lo, hi, 0x7362);
}
__device__ __forceinline__ uint4 dequant8(uint32_t p, const uint4& sc, const Lut& t) {
    const uint32_t m8 = p & 0x88888888u, s7 = p & 0x77777777u;
    uint4 r;
    lookup4(s7, (m8 >> 1) + 0x3210u, t, r.x, r.y);
    lookup4(s7 >> 16, (m8 >> 17) + 0x3210u, t, r.z, r.w);
    r.x = mul_bf16x2(r.x, sc.x); r.y = mul_bf16x2(r.y, sc.y); r.z = mul_bf16x2(r.z, sc.z); r.w = mul_bf16x2(r.w, sc.w);
    return r;
}
__device__ __forceinline__ uint4 dequant8_shfl(const uint4& q0, const uint4& q1, const uint4& sc, uint32_t tab) {
    uint4 r;
    r.x = mul_bf16x2(__byte_perm(__shfl_sync(~0u, tab, q0.x), __shfl_sync(~0u, tab, q0.y), 0x5410), sc.x);
    r.y = mul_bf16x2(__byte_perm(__shfl_sync(~0u, tab, q0.z), __shfl_sync(~0u, tab, q0.w), 0x5410), sc.y);
    r.z = mul_bf16x2(__byte_perm(__shfl_sync(~0u, tab, q1.x), __shfl_sync(~0u, tab, q1.y), 0x5410), sc.z);
    r.w = mul_bf16x2(__byte_perm(__shfl_sync(~0u, tab, q1.z), __shfl_sync(~0u, tab, q1.w), 0x5410), sc.w);
    return r;
}

__device__ __forceinline__ void wgmma_fence() { asm volatile("wgmma.fence.sync.aligned;" ::: "memory"); }
__device__ __forceinline__ void wgmma_commit() { asm volatile("wgmma.commit_group.sync.aligned;" ::: "memory"); }
template <int N> __device__ __forceinline__ void wgmma_wait() { asm volatile("wgmma.wait_group.sync.aligned %0;" ::"n"(N) : "memory"); }
template <int SCALE_D>
__device__ __forceinline__ void wgmma_ss(float (&d)[112], uint32_t descA, uint32_t descB) {
    asm volatile(
        "{\n.reg .pred p;\n.reg .b64 da, db;\nsetp.ne.b32 p, %114, 0;\n"
        "mov.b64 da, {%112, 0x40000040};\nmov.b64 db, {%113, 0x10};\n"
        "wgmma.mma_async.sync.aligned.m64n224k16.f32.bf16.bf16 "
        "{%0, %1, %2, %3, %4, %5, %6, %7, %8, %9, %10, %11, %12, %13, %14, %15, "
        "%16, %17, %18, %19, %20, %21, %22, %23, %24, %25, %26, %27, %28, %29, %30, %31, "
        "%32, %33, %34, %35, %36, %37, %38, %39, %40, %41, %42, %43, %44, %45, %46, %47, "
        "%48, %49, %50, %51, %52, %53, %54, %55, %56, %57, %58, %59, %60, %61, %62, %63, "
        "%64, %65, %66, %67, %68, %69, %70, %71, %72, %73, %74, %75, %76, %77, %78, %79, "
        "%80, %81, %82, %83, %84, %85, %86, %87, %88, %89, %90, %91, %92, %93, %94, %95, "
        "%96, %97, %98, %99, %100, %101, %102, %103, %104, %105, %106, %107, %108, %109, %110, %111}, "
        "da, db, p, 1, 1, 0, 1;\n}\n"
        : "+f"(d[0]), "+f"(d[1]), "+f"(d[2]), "+f"(d[3]), "+f"(d[4]), "+f"(d[5]), "+f"(d[6]), "+f"(d[7]),
          "+f"(d[8]), "+f"(d[9]), "+f"(d[10]), "+f"(d[11]), "+f"(d[12]), "+f"(d[13]), "+f"(d[14]), "+f"(d[15]),
          "+f"(d[16]), "+f"(d[17]), "+f"(d[18]), "+f"(d[19]), "+f"(d[20]), "+f"(d[21]), "+f"(d[22]), "+f"(d[23]),
          "+f"(d[24]), "+f"(d[25]), "+f"(d[26]), "+f"(d[27]), "+f"(d[28]), "+f"(d[29]), "+f"(d[30]), "+f"(d[31]),
          "+f"(d[32]), "+f"(d[33]), "+f"(d[34]), "+f"(d[35]), "+f"(d[36]), "+f"(d[37]), "+f"(d[38]), "+f"(d[39]),
          "+f"(d[40]), "+f"(d[41]), "+f"(d[42]), "+f"(d[43]), "+f"(d[44]), "+f"(d[45]), "+f"(d[46]), "+f"(d[47]),
          "+f"(d[48]), "+f"(d[49]), "+f"(d[50]), "+f"(d[51]), "+f"(d[52]), "+f"(d[53]), "+f"(d[54]), "+f"(d[55]),
          "+f"(d[56]), "+f"(d[57]), "+f"(d[58]), "+f"(d[59]), "+f"(d[60]), "+f"(d[61]), "+f"(d[62]), "+f"(d[63]),
          "+f"(d[64]), "+f"(d[65]), "+f"(d[66]), "+f"(d[67]), "+f"(d[68]), "+f"(d[69]), "+f"(d[70]), "+f"(d[71]),
          "+f"(d[72]), "+f"(d[73]), "+f"(d[74]), "+f"(d[75]), "+f"(d[76]), "+f"(d[77]), "+f"(d[78]), "+f"(d[79]),
          "+f"(d[80]), "+f"(d[81]), "+f"(d[82]), "+f"(d[83]), "+f"(d[84]), "+f"(d[85]), "+f"(d[86]), "+f"(d[87]),
          "+f"(d[88]), "+f"(d[89]), "+f"(d[90]), "+f"(d[91]), "+f"(d[92]), "+f"(d[93]), "+f"(d[94]), "+f"(d[95]),
          "+f"(d[96]), "+f"(d[97]), "+f"(d[98]), "+f"(d[99]), "+f"(d[100]), "+f"(d[101]), "+f"(d[102]), "+f"(d[103]),
          "+f"(d[104]), "+f"(d[105]), "+f"(d[106]), "+f"(d[107]), "+f"(d[108]), "+f"(d[109]), "+f"(d[110]), "+f"(d[111])
        : "r"(descA), "r"(descB), "n"(SCALE_D));
}

template <int SCALE_D>
__device__ __forceinline__ void wgmma_ss(float (&d)[64], uint32_t descA, uint32_t descB) {
    asm volatile(
        "{\n.reg .pred p;\n.reg .b64 da, db;\nsetp.ne.b32 p, %66, 0;\n"
        "mov.b64 da, {%64, 0x40000040};\nmov.b64 db, {%65, 0x10};\n"
        "wgmma.mma_async.sync.aligned.m64n128k16.f32.bf16.bf16 "
        "{%0, %1, %2, %3, %4, %5, %6, %7, %8, %9, %10, %11, %12, %13, %14, %15, "
        "%16, %17, %18, %19, %20, %21, %22, %23, %24, %25, %26, %27, %28, %29, %30, %31, "
        "%32, %33, %34, %35, %36, %37, %38, %39, %40, %41, %42, %43, %44, %45, %46, %47, "
        "%48, %49, %50, %51, %52, %53, %54, %55, %56, %57, %58, %59, %60, %61, %62, %63}, "
        "da, db, p, 1, 1, 0, 1;\n}\n"
        : "+f"(d[0]), "+f"(d[1]), "+f"(d[2]), "+f"(d[3]), "+f"(d[4]), "+f"(d[5]), "+f"(d[6]), "+f"(d[7]),
          "+f"(d[8]), "+f"(d[9]), "+f"(d[10]), "+f"(d[11]), "+f"(d[12]), "+f"(d[13]), "+f"(d[14]), "+f"(d[15]),
          "+f"(d[16]), "+f"(d[17]), "+f"(d[18]), "+f"(d[19]), "+f"(d[20]), "+f"(d[21]), "+f"(d[22]), "+f"(d[23]),
          "+f"(d[24]), "+f"(d[25]), "+f"(d[26]), "+f"(d[27]), "+f"(d[28]), "+f"(d[29]), "+f"(d[30]), "+f"(d[31]),
          "+f"(d[32]), "+f"(d[33]), "+f"(d[34]), "+f"(d[35]), "+f"(d[36]), "+f"(d[37]), "+f"(d[38]), "+f"(d[39]),
          "+f"(d[40]), "+f"(d[41]), "+f"(d[42]), "+f"(d[43]), "+f"(d[44]), "+f"(d[45]), "+f"(d[46]), "+f"(d[47]),
          "+f"(d[48]), "+f"(d[49]), "+f"(d[50]), "+f"(d[51]), "+f"(d[52]), "+f"(d[53]), "+f"(d[54]), "+f"(d[55]),
          "+f"(d[56]), "+f"(d[57]), "+f"(d[58]), "+f"(d[59]), "+f"(d[60]), "+f"(d[61]), "+f"(d[62]), "+f"(d[63])
        : "r"(descA), "r"(descB), "n"(SCALE_D));
}

__device__ __forceinline__ void wgmma_rs(float (&d)[64], const uint4& a, uint32_t descB) {
    asm volatile(
        "{\n.reg .pred p;\n.reg .b64 db;\nsetp.eq.b32 p, 0, 0;\n"
        "mov.b64 db, {%68, 0x10};\n"
        "wgmma.mma_async.sync.aligned.m64n128k16.f32.bf16.bf16 "
        "{%0, %1, %2, %3, %4, %5, %6, %7, %8, %9, %10, %11, %12, %13, %14, %15, "
        "%16, %17, %18, %19, %20, %21, %22, %23, %24, %25, %26, %27, %28, %29, %30, %31, "
        "%32, %33, %34, %35, %36, %37, %38, %39, %40, %41, %42, %43, %44, %45, %46, %47, "
        "%48, %49, %50, %51, %52, %53, %54, %55, %56, %57, %58, %59, %60, %61, %62, %63}, "
        "{%64, %65, %66, %67}, db, p, 1, 1, 1;\n}\n"
        : "+f"(d[0]), "+f"(d[1]), "+f"(d[2]), "+f"(d[3]), "+f"(d[4]), "+f"(d[5]), "+f"(d[6]), "+f"(d[7]),
          "+f"(d[8]), "+f"(d[9]), "+f"(d[10]), "+f"(d[11]), "+f"(d[12]), "+f"(d[13]), "+f"(d[14]), "+f"(d[15]),
          "+f"(d[16]), "+f"(d[17]), "+f"(d[18]), "+f"(d[19]), "+f"(d[20]), "+f"(d[21]), "+f"(d[22]), "+f"(d[23]),
          "+f"(d[24]), "+f"(d[25]), "+f"(d[26]), "+f"(d[27]), "+f"(d[28]), "+f"(d[29]), "+f"(d[30]), "+f"(d[31]),
          "+f"(d[32]), "+f"(d[33]), "+f"(d[34]), "+f"(d[35]), "+f"(d[36]), "+f"(d[37]), "+f"(d[38]), "+f"(d[39]),
          "+f"(d[40]), "+f"(d[41]), "+f"(d[42]), "+f"(d[43]), "+f"(d[44]), "+f"(d[45]), "+f"(d[46]), "+f"(d[47]),
          "+f"(d[48]), "+f"(d[49]), "+f"(d[50]), "+f"(d[51]), "+f"(d[52]), "+f"(d[53]), "+f"(d[54]), "+f"(d[55]),
          "+f"(d[56]), "+f"(d[57]), "+f"(d[58]), "+f"(d[59]), "+f"(d[60]), "+f"(d[61]), "+f"(d[62]), "+f"(d[63])
        : "r"(a.x), "r"(a.y), "r"(a.z), "r"(a.w), "r"(descB));
}

__device__ __forceinline__ void wgmma_rs(float (&d)[32], const uint4& a, uint32_t descB) {
    asm volatile(
        "{\n.reg .pred p;\n.reg .b64 db;\nsetp.eq.b32 p, 0, 0;\n"
        "mov.b64 db, {%36, 0x10};\n"
        "wgmma.mma_async.sync.aligned.m64n64k16.f32.bf16.bf16 "
        "{%0, %1, %2, %3, %4, %5, %6, %7, %8, %9, %10, %11, %12, %13, %14, %15, "
        "%16, %17, %18, %19, %20, %21, %22, %23, %24, %25, %26, %27, %28, %29, %30, %31}, "
        "{%32, %33, %34, %35}, db, p, 1, 1, 1;\n}\n"
        : "+f"(d[0]), "+f"(d[1]), "+f"(d[2]), "+f"(d[3]), "+f"(d[4]), "+f"(d[5]), "+f"(d[6]), "+f"(d[7]),
          "+f"(d[8]), "+f"(d[9]), "+f"(d[10]), "+f"(d[11]), "+f"(d[12]), "+f"(d[13]), "+f"(d[14]), "+f"(d[15]),
          "+f"(d[16]), "+f"(d[17]), "+f"(d[18]), "+f"(d[19]), "+f"(d[20]), "+f"(d[21]), "+f"(d[22]), "+f"(d[23]),
          "+f"(d[24]), "+f"(d[25]), "+f"(d[26]), "+f"(d[27]), "+f"(d[28]), "+f"(d[29]), "+f"(d[30]), "+f"(d[31])
        : "r"(a.x), "r"(a.y), "r"(a.z), "r"(a.w), "r"(descB));
}

__device__ __forceinline__ void wgmma_rs(float (&d)[16], const uint4& a, uint32_t descB) {
    asm volatile(
        "{\n.reg .pred p;\n.reg .b64 db;\nsetp.eq.b32 p, 0, 0;\n"
        "mov.b64 db, {%20, 0x10};\n"
        "wgmma.mma_async.sync.aligned.m64n32k16.f32.bf16.bf16 "
        "{%0, %1, %2, %3, %4, %5, %6, %7, %8, %9, %10, %11, %12, %13, %14, %15}, "
        "{%16, %17, %18, %19}, db, p, 1, 1, 1;\n}\n"
        : "+f"(d[0]), "+f"(d[1]), "+f"(d[2]), "+f"(d[3]), "+f"(d[4]), "+f"(d[5]), "+f"(d[6]), "+f"(d[7]),
          "+f"(d[8]), "+f"(d[9]), "+f"(d[10]), "+f"(d[11]), "+f"(d[12]), "+f"(d[13]), "+f"(d[14]), "+f"(d[15])
        : "r"(a.x), "r"(a.y), "r"(a.z), "r"(a.w), "r"(descB));
}

constexpr int NT = N_ / BN, MT = M_ / BM;
constexpr int W_BYTES = BN * BK * 2;
constexpr int SLAB = 8 * BN * 4;
constexpr int SC_ROW = BN * 2;
constexpr int X_OFF = 0;
constexpr int W_OFF = 10 * 8192;
constexpr int R_OFF = W_OFF + 4 * W_BYTES;
constexpr int SC_OFF = R_OFF + W_BYTES - 2 * SC_ROW;
constexpr int RAW0_OFF = W_OFF + 2 * W_BYTES;
constexpr int SC0_OFF = W_OFF + 3 * W_BYTES;
constexpr int BAR_OFF = SC_OFF + 16 * SC_ROW;
constexpr int SMEM_BYTES = BAR_OFF + 896;
constexpr unsigned READY = MT * 7;
constexpr int UM = 22;
constexpr int NAG = 7;

__device__ __align__(1024) uint8_t g_wimg[(size_t)NT * KC * W_BYTES];
__device__ unsigned g_flag[NT * 32];

__host__ __device__ constexpr int slab_at(int u) { return u == 0 ? 2 : u == 1 ? 3 : u == 3 ? 4 : u == 5 ? 5 : (u >= 7 && u <= 16) ? u - 1 : -1; }
__host__ __device__ constexpr int wload_at(int u) {
    return u <= 10 ? ((u & 1) ? -1 : u / 2 + 1) : u <= 17 ? ((u & 1) ? (u + 3) / 2 : -1) : u == 18 ? 11 : u == 19 ? 12 : u == 20 ? 15 : u == 21 ? 13 : -1;
}
__host__ __device__ constexpr int tail_chunk(int j) { return j == 3 ? 15 : j == 4 ? 14 : 11 + j; }
__host__ __device__ constexpr int wbuf(int c) { return c == 15 ? 4 : c & 3; }

template <int NR>
__device__ __forceinline__ void store_cols(const float (&acc)[NR], uint8_t* p) {
#pragma unroll
    for (int j = 0; j < NR / 16; j++) {
        const int i = 16 * j;
        stg128(p + j * 64, pack_bf16(acc[i], acc[i + 1]), pack_bf16(acc[i + 4], acc[i + 5]), pack_bf16(acc[i + 8], acc[i + 9]), pack_bf16(acc[i + 12], acc[i + 13]));
        stg128(p + j * 64 + 8 * N_ * 2, pack_bf16(acc[i + 2], acc[i + 3]), pack_bf16(acc[i + 6], acc[i + 7]), pack_bf16(acc[i + 10], acc[i + 11]), pack_bf16(acc[i + 14], acc[i + 15]));
    }
}

__global__ void __cluster_dims__(2, 1, 1) __launch_bounds__(256, 1)
nf4_gemm_kernel(const uint8_t* __restrict__ qw, const __nv_bfloat16* __restrict__ cb, const __nv_bfloat16* __restrict__ absmax,
                uint8_t* __restrict__ wimg, unsigned* __restrict__ gflags, uint8_t* __restrict__ out, const unsigned zero,
                const __grid_constant__ CUtensorMap tmx, const __grid_constant__ CUtensorMap tmx64, const __grid_constant__ CUtensorMap tmq16,
                const __grid_constant__ CUtensorMap tmq8, const __grid_constant__ CUtensorMap tmq1, const __grid_constant__ CUtensorMap tms) {
    extern __shared__ __align__(1024) uint8_t smem[];
    const int rank = blockIdx.x & 1;
    const int mt = (blockIdx.x & 3) + (blockIdx.x >> 6) * 4, nt = (blockIdx.x >> 2) & 15;
    const uint8_t* share;
    asm volatile(
        "{\n.reg .b32 t, b, o, h;\n.reg .b64 a;\n.reg .pred p;\n"
        "mov.u32 t, %%tid.x;\nmov.u32 b, %%ctaid.x;\n"
        "shr.u32 h, t, 5;\nshl.b32 o, t, 5;\nmad.lo.u32 o, h, %2 - 1024, o;\n"
        "and.b32 h, b, 3;\nmad.lo.u32 o, h, 8 * %2 - %3 / 4, o;\n"
        "shr.u32 h, b, 6;\nmad.lo.u32 o, h, 32 * %2 - 16 * %3, o;\n"
        "mad.lo.u32 o, b, %3 / 4, o;\n"
        "cvt.u64.u32 a, o;\nadd.u64 a, a, %1;\n"
        "prefetch.global.L2 [a + 64 * %2];\n"
        "setp.lt.u32 p, b, 64;\n@p prefetch.global.L2 [a + 96 * %2];\n"
        "mov.b64 %0, a;\n}\n" : "=l"(share) : "l"(qw), "n"(N_ * 4), "n"(BN * 4));
    const uint32_t sbase = smem_u32(smem);
    const int warp = __shfl_sync(~0u, (int)(threadIdx.x >> 5), 0);
    const int wg = warp >> 2, wj = warp & 3;
    const int lane = threadIdx.x & 31;
    const uint32_t bars = sbase + BAR_OFF;
    const uint32_t snap = bars;
    const uint32_t xfull = bars + 64 + wg * 40;
    const uint32_t wfull = bars + 144;
    const uint32_t wempty = bars + 184;
    const uint32_t ringfull = bars + 216;
    const uint32_t rawbar = bars + 248;
    const uint32_t wown = bars + 264;
    const uint32_t stored = bars + 272 - 8;
    const uint32_t wlast = bars + 344;
    const uint32_t xbase = sbase + X_OFF + wg * 40960, wbase = sbase + W_OFF, rbase = sbase + R_OFF;
    const int xrow = mt * BM + wg * 128 + wj * 16;
    const uint8_t* wsrc = wimg + (size_t)nt * KC * W_BYTES;
    unsigned* flags = gflags + nt * 32;

    auto load_x = [&](int u, int cs = -1) {
        const int c = u < UM ? u >> 1 : tail_chunk((u - UM) % 5), b = u < UM ? u & 1 : (u - UM) / 5;
        mbar_expect_tx(xfull + 8 * (u % 5), cs >= 0 ? 3072 : 2048);
        tma_load_2d(xbase + (u % 5) * 8192 + wj * 2048, &tmx, c * BK, xrow + b * 64, xfull + 8 * (u % 5));
        if (cs >= 0) tma_load_2d(rbase + (cs & 3) * SLAB + warp * 1024, &tmq1, nt * BN + warp * 32, cs * BK + mt * 8, xfull + 8 * (u % 5));
    };
    auto load_x64 = [&](int g, int u) {
        const uint32_t bar = bars + 64 + g * 40 + 8 * u;
        mbar_arrive_n(bar, 3);
        mbar_expect_tx(bar, 8192);
        tma_load_2d(sbase + X_OFF + g * 40960 + u * 8192, &tmx64, (u >> 1) * BK, mt * BM + g * 128 + (u & 1) * 64, bar);
    };
    auto load_slab = [&](int c, uint32_t extra = 0) {
        mbar_expect_tx(ringfull + 8 * (c & 3), SLAB + extra);
        tma_load_3d(rbase + (c & 3) * SLAB, &tmq8, 0, c * BK + mt * 8, nt * 7, ringfull + 8 * (c & 3));
    };
    auto load_raw = [&](int p, uint32_t extra = 0) {
        mbar_expect_tx(rawbar + 8 * p, 2 * SLAB + extra);
        tma_load_3d(sbase + RAW0_OFF + p * 2 * SLAB, &tmq16, 0, rank * 32 + p * 16, nt * 7, rawbar + 8 * p);
    };
    if (warp == 7) {
        if (elect()) {
            mbar_init(ringfull + 8, 1); mbar_init(rawbar, 1); mbar_init(rawbar + 8, 1);
            load_slab(1, SC_ROW);
            bulk_load(sbase + SC0_OFF + SC_ROW, absmax + N_ + nt * BN, SC_ROW, ringfull + 8);
            load_raw(0, SC_ROW);
            bulk_load(sbase + SC0_OFF, absmax + nt * BN, SC_ROW, rawbar);
            load_raw(1);
            mbar_init(bars + 64, 4); mbar_init(bars + 72, 4); mbar_init(bars + 104, 4); mbar_init(bars + 112, 4); mbar_init(ringfull + 16, 1);
            mbar_init_fence();
        }
        __syncwarp();
    }
    uint4 c0, c1;
    asm volatile("ld.global.nc.v4.u32 {%0, %1, %2, %3}, [%8];\nld.global.nc.v4.u32 {%4, %5, %6, %7}, [%8 + 16];"
                 : "=r"(c0.x), "=r"(c0.y), "=r"(c0.z), "=r"(c0.w), "=r"(c1.x), "=r"(c1.y), "=r"(c1.z), "=r"(c1.w) : "l"(cb));
    if (warp < 7) delay(200);
    asm volatile("prefetch.global.L2 [%0];" ::"l"(share));
    if (blockIdx.x < 64) asm volatile("prefetch.global.L2 [%0];" ::"l"(share + 32 * N_ * 4));
    if (warp == 5 || warp == 6) {
        if (elect()) {
            if (warp == 6) {
#pragma unroll
                for (int s = 0; s < 5; s++) mbar_init(wfull + 8 * s, 1);
#pragma unroll
                for (int s = 0; s < 4; s++) mbar_init(wempty + 8 * s, 16);
                mbar_init(wown, 7); mbar_init(wlast, 1); mbar_init(ringfull, 1); mbar_init(ringfull + 24, 1);
                mbar_expect_tx(wfull, W_BYTES / 2);
            }
            if (warp == 5) {
#pragma unroll
                for (int s = 0; s < 10; s++) if (s % 5 >= 2) mbar_init(bars + 64 + 8 * s, 4);
#pragma unroll
                for (int s = 1; s <= NAG; s++) mbar_init(stored + 8 * s, s == 1 ? 7 : 224);
            }
            mbar_init_fence();
        }
        __syncwarp();
    }
    cluster_arrive();
    if (warp == 7) {
        if (elect()) { load_x64(0, 0); load_x64(0, 1); load_x64(1, 0); load_x64(1, 1); }
        __syncwarp();
    }
    const uint32_t rlane = (lane & 7) * 128 + ((((lane >> 3) * 2) ^ (lane & 7)) << 4);
    const uint32_t wlane = warp * 1024 + (lane & 7) * 16 + (lane >> 3) * 4;
    const uint32_t slabsrc = __shfl_sync(~0u, (warp < 7 ? warp * 1024 + rlane : 0) + sbase, lane);
    const uint32_t scsrc = __shfl_sync(~0u, sbase + (warp < 7 ? warp * 64 : 0) + (lane >> 3) * 16, lane);
    uint8_t* const gdst = wimg + (size_t)nt * KC * W_BYTES + (mt >> 1) * SLAB + (mt & 1) * 128 + wlane;
    uint8_t* const gkeep = (uint8_t*)__shfl_sync(~0u, (unsigned long long)gdst, lane);
    uint8_t* const gread = (uint8_t*)__shfl_sync(~0u, (unsigned long long)(warp < 7 ? gdst + (lane >> 3) * 252 : (uint8_t*)flags + (lane >> 3) * 16), lane);
    Lut lut = {};
    if (warp < 7) {
        lut.lo[0] = __byte_perm(c0.x, c0.y, 0x6420); lut.hi[0] = __byte_perm(c0.x, c0.y, 0x7531);
        lut.lo[1] = __byte_perm(c0.z, c0.w, 0x6420); lut.hi[1] = __byte_perm(c0.z, c0.w, 0x7531);
        lut.lo[2] = __byte_perm(c1.x, c1.y, 0x6420); lut.hi[2] = __byte_perm(c1.x, c1.y, 0x7531);
        lut.lo[3] = __byte_perm(c1.z, c1.w, 0x6420); lut.hi[3] = __byte_perm(c1.z, c1.w, 0x7531);
    }
    cluster_wait();

    auto store_slab = [&](int c, uint32_t p, const uint4& sc) {
        const uint4 w = dequant8(p, sc, lut);
        uint8_t* g = gkeep + (size_t)c * W_BYTES;
        stg32(g, w.x); stg32(g + 256, w.y); stg32(g + 512, w.z); stg32(g + 768, w.w);
        if (c == 1) {
            __syncwarp();
            if (elect()) mbar_arrive(stored + 8);
            __syncwarp();
        } else {
            read_l2(scsrc + SC_OFF + SC_ROW * c, gread + (size_t)c * W_BYTES, (lane & 7) == 0);
            if (c <= NAG) read_arrive(stored + 8 * c);
        }
    };
    auto take_sample = [&]() { read_l2(scsrc + BAR_OFF, gread, (lane & 7) == 0); };
    auto load_w = [&](int c) {
        read_wait<0>();
        poll_ge(flags + c, lds32(snap + 4 * c), READY);
        asm volatile("fence.acquire.gpu;" ::: "memory");
        asm volatile("fence.proxy.async.global;" ::: "memory");
        if (c >= 4 && c < 15) mbar_wait(wempty + 8 * (c & 3), ((c >> 2) - 1) & 1);
        if (elect()) {
            if (c == 1) {
                mbar_expect_tx(wfull + 8, W_BYTES / 2);
                bulk_load_mc(wbase + W_BYTES + rank * SLAB, wsrc + W_BYTES + rank * SLAB, SLAB, wfull + 8);
                mbar_expect_tx(wlast, W_BYTES / 2);
                bulk_load_mc(wbase + W_BYTES + (2 + rank) * SLAB, wsrc + W_BYTES + (2 + rank) * SLAB, SLAB, wlast);
            } else {
                mbar_expect_tx(wfull + 8 * wbuf(c), W_BYTES);
                bulk_load_mc(wbase + wbuf(c) * W_BYTES + rank * (W_BYTES / 2), wsrc + (size_t)c * W_BYTES + rank * (W_BYTES / 2), W_BYTES / 2, wfull + 8 * wbuf(c));
            }
        }
        __syncwarp();
    };

    if (warp < 7) {
        mbar_wait(ringfull + 8, 0);
        store_slab(1, pack8(lds128(slabsrc + R_OFF + SLAB), lds128((slabsrc ^ 16) + R_OFF + SLAB)), lds128(scsrc + SC0_OFF + SC_ROW));
        const uint32_t tab = prmt(prmt(lane & 8 ? lut.lo[2] : lut.lo[0], lane & 8 ? lut.lo[3] : lut.lo[1], lane & 7),
                                  prmt(lane & 8 ? lut.hi[2] : lut.hi[0], lane & 8 ? lut.hi[3] : lut.hi[1], lane & 7), 0x40);
        uint4 sc;
#pragma unroll
        for (int p = 0; p < 2; p++) {
            mbar_wait(rawbar + 8 * p, 0);
            if (p == 0) { sc = lds128(scsrc + SC0_OFF); }
            const uint32_t a = sbase + RAW0_OFF + p * 2 * SLAB + warp * 2048;
            const uint4 v0 = lds128(a + rlane), v1 = lds128(a + (rlane ^ 16)), v2 = lds128(a + rlane + 1024), v3 = lds128(a + (rlane ^ 16) + 1024);
            const uint4 w0 = dequant8(pack8(v0, v1), sc, lut), w1 = dequant8_shfl(v2, v3, sc, tab);
            const uint32_t d = wbase + (2 * rank + p) * SLAB, e = d + wlane;
            sts32(e, w0.x); sts32(e + 256, w0.y); sts32(e + 512, w0.z); sts32(e + 768, w0.w);
            sts32(e + 128, w1.x); sts32(e + 384, w1.y); sts32(e + 640, w1.z); sts32(e + 896, w1.w);
            fence_async_smem();
            __syncwarp();
            if (elect()) {
                if (p == 1) mbar_arrive(wown);
                copy_to_peer(d + warp * 1024, 1024, wfull, rank ^ 1);
            }
            __syncwarp();
        }
    } else {
        mbar_wait(stored + 8, 0);
        const unsigned v = ld_relaxed(wsrc + W_BYTES + (mt >> 1) * SLAB + (mt & 1) * 128 + (lane < 28 ? lane : 0) * 256);
        if (elect()) {
            load_slab(2, 14 * SC_ROW);
            tma_load_2d(sbase + SC_OFF + 2 * SC_ROW, &tms, nt * BN, 2, ringfull + 16);
        }
        __syncwarp();
        const unsigned n = after(7, v, zero);
        __syncwarp();
        if (elect()) red_add(flags + 1, n);
        __syncwarp();
        if (elect()) { load_x64(0, 2); load_x64(1, 2); load_x64(0, 3); load_x64(1, 3); load_slab(3); }
        __syncwarp();
    }

    float acc0[112], acc1[112];
    const uint32_t descA = ((xbase & 0x3FFFF) >> 4) | (1u << 16), descB = ((wbase & 0x3FFFF) >> 4) | ((128u >> 4) << 16);
    static_for<0, UM>([&](auto U) __attribute__((always_inline)) {
        constexpr int u = U.value, kc = u >> 1;
        constexpr int c = slab_at(u);
        uint32_t da = descA, db = descB;
        asm volatile("" : "+r"(da), "+r"(db));
        uint4 q0, q1, sc;
        auto slab_loads = [&]() {
            q0 = lds128(slabsrc + R_OFF + (c & 3) * SLAB); q1 = lds128((slabsrc ^ 16) + R_OFF + (c & 3) * SLAB);
            sc = lds128(scsrc + SC_OFF + SC_ROW * (c & 15));
        };
        if (u < 4) {
            if (u == 0) mbar_wait3(xfull, 0, xfull + 8, 0, wown, 0);
            if (u == 1) mbar_wait(wfull, 0);
            if (u == 2) mbar_wait3(xfull + 16, 0, xfull + 24, 0, wfull + 8, 0);
            if (u == 3) { mbar_wait2(wlast, 0, ringfull, 0); slab_loads(); }
            if (u == 0 && warp == 7) take_sample();
            const int h = u < 2 ? rank ^ u : u & 1;
            da += kc * 1024 + h * 4; db += kc * (W_BYTES >> 4) + h * (2 * SLAB >> 4);
            wgmma_fence();
            wgmma_ss<u != 0>(acc0, da, db); wgmma_ss<u != 0>(acc1, da + 512, db);
            wgmma_ss<1>(acc0, da + 2, db + (SLAB >> 4)); wgmma_ss<1>(acc1, da + 514, db + (SLAB >> 4));
        } else {
            if (u & 1) mbar_wait(xfull + 8 * (u % 5), (u / 5) & 1);
            else mbar_wait2(xfull + 8 * (u % 5), (u / 5) & 1, wfull + 8 * (kc & 3), (kc >> 2) & 1);
            if (c >= 0) slab_loads();
            da += (u % 5) * 512; db += (kc & 3) * (W_BYTES >> 4);
            wgmma_fence();
#pragma unroll
            for (int ks = 0; ks < 4; ks++) {
                if (u & 1) wgmma_ss<1>(acc1, da + ks * 2, db + ks * (SLAB >> 4));
                else wgmma_ss<1>(acc0, da + ks * 2, db + ks * (SLAB >> 4));
            }
        }
        wgmma_commit();
        if (u >= 2) wgmma_wait<1>();
        if (warp < 7) {
            constexpr int cp = slab_at(u - 2) > NAG ? slab_at(u - 2) : -1;
            if constexpr (u < 2) { mbar_wait(ringfull + 8 * c, 0); slab_loads(); }
            uint32_t p = 0;
            if (c >= 0) p = pack8(q0, q1);
            if (cp >= 0) { if (slab_at(u - 1) >= 0) read_wait<1>(); else read_wait<0>(); }
            if (u >= 2) {
                if (elect()) {
                    if (u <= 17) load_x(u + 3, slab_at(u + 3));
                    if (u >= 17) load_x(u + 4);
                    if (!(u & 1)) mbar_arrive_both(wempty + 8 * ((kc - 1) & 3));
                    if (cp >= 0) red_add(flags + cp, 1);
                }
                __syncwarp();
            }
            if (c >= 0) store_slab(c, p, sc);
        } else {
            constexpr int cw = wload_at(u), cc = slab_at(u - 1) <= NAG ? slab_at(u - 1) : -1;
            if (cw >= 0 && cw <= 6) load_w(cw);
            if (u != 1) {
                if (elect()) {
                    if (u == 0) load_slab(4);
                    if (u >= 2 && u <= 17) load_x(u + 3);
                    if (u >= 17) load_x(u + 4);
                    if (u >= 2 && !(u & 1)) mbar_arrive_both(wempty + 8 * ((kc - 1) & 3));
                }
                __syncwarp();
            }
            if constexpr (cc >= 0) {
                mbar_wait(stored + 8 * cc, 0);
                if (elect()) red_add(flags + cc, 7);
                __syncwarp();
            }
            if (u == 1) {
                if (elect()) { load_x64(0, 4); load_x64(1, 4); }
                __syncwarp();
                delay(300);
            }
            if (cw > 6) load_w(cw);
            if (wload_at(u + 1) >= 0) take_sample();
        }
    });

    uint32_t tA = descA, tB = descB;
    asm volatile("" : "+r"(tA), "+r"(tB));
    if (wg == 1) {
        wgmma_wait<0>();
        if (elect()) { load_x(UM + 4); mbar_arrive_both(wempty + 16); }
        __syncwarp();
        if (warp == 7) load_w(14);
        if (warp == 7 && lane == 0) {
            if (atomicAdd(flags + 16, 1) == MT - 1) {
#pragma unroll
                for (int c = 0; c <= 16; c++) flags[c] = 0;
            }
        }
        __syncwarp();
        bar_sync<256>(1);
    }
#pragma unroll
    for (int j = 0; j < 5; j++) {
        const int c = tail_chunk(j), v = UM + j;
        mbar_wait2(xfull + 8 * (v % 5), (v / 5) & 1, wfull + 8 * wbuf(c), c == 15 ? 0 : (c >> 2) & 1);
        wgmma_fence();
#pragma unroll
        for (int ks = 0; ks < 4; ks++) wgmma_ss<1>(acc0, tA + (v % 5) * 512 + ks * 2, tB + wbuf(c) * (W_BYTES >> 4) + ks * (SLAB >> 4));
        wgmma_commit();
        if (j == 4) bar_arrive<256>(1 + wg);
        if (j == 0) {
            if (wg == 0) {
                wgmma_wait<1>();
                if (elect()) { load_x(UM + 4); mbar_arrive_both(wempty + 16); }
                __syncwarp();
            }
        } else if (j >= 2) {
            wgmma_wait<2>();
            if (elect()) load_x(v + 3);
            __syncwarp();
        }
    }
    wgmma_wait<1>();
    if (elect()) load_x(UM + 8);
    __syncwarp();
    wgmma_wait<0>();
    if (elect()) load_x(UM + 9);
    __syncwarp();
    uint8_t* optr = out + (size_t)(xrow + (lane >> 2)) * (N_ * 2) + nt * (BN * 2) + (lane & 3) * 16;
    float pa[64], pb[32], pc[16];
#pragma unroll
    for (int i = 0; i < 64; i++) asm volatile("mov.b32 %0, %1;" : "=f"(pa[i]) : "f"(acc1[i]));
#pragma unroll
    for (int i = 0; i < 32; i++) asm volatile("mov.b32 %0, %1;" : "=f"(pb[i]) : "f"(acc1[64 + i]));
#pragma unroll
    for (int i = 0; i < 16; i++) asm volatile("mov.b32 %0, %1;" : "=f"(pc[i]) : "f"(acc1[96 + i]));
    uint4 af[20];
    uint32_t pk[56];
    auto store_pk = [&](int h0, int h1) {
#pragma unroll
        for (int h = h0; h < h1; h++) {
            const int i = 8 * (h >> 1) + (h & 1);
            stg128(optr + (h >> 1) * 64 + (h & 1) * (8 * N_ * 2), pk[i], pk[i + 2], pk[i + 4], pk[i + 6]);
        }
    };
    const uint32_t alane = xbase + wj * 2048 + (lane & 15) * 128 + (((lane >> 4) ^ (lane & 7)) << 4);
    static_for<0, 4>([&](auto J) __attribute__((always_inline)) {
        constexpr int j = J.value, v = UM + 5 + j;
        mbar_wait(xfull + 8 * (v % 5), (v / 5) & 1);
#pragma unroll
        for (int ks = 0; ks < 4; ks++) af[4 * j + ks] = ldmatrix_x4((alane ^ (ks * 32)) + (v % 5) * 8192);
#pragma unroll
        for (int i = 16 * j; i < (j < 3 ? 16 * j + 16 : 56); i++) pk[i] = pack_bf16(acc0[2 * i], acc0[2 * i + 1]);
        store_pk(2 * j, 2 * j + 2);
    });
    store_pk(8, 10);
    if (wg == 0) store_pk(10, 14);
    auto piece = [&](auto& d, auto CB) {
        constexpr int cb = CB.value;
        wgmma_fence();
#pragma unroll
        for (int j = 0; j < 5; j++) {
            if (cb == 0 && j == 4) { mbar_wait(xfull + 8 * ((UM + 9) % 5), ((UM + 9) / 5) & 1); wgmma_fence(); }
#pragma unroll
            for (int ks = 0; ks < 4; ks++) {
                const uint32_t db = tB + wbuf(tail_chunk(j)) * (W_BYTES >> 4) + ks * (SLAB >> 4) + cb * 64;
                if (j < 4 || cb > 0) wgmma_rs(d, af[4 * j + ks], db);
                else if constexpr (cb == 0) wgmma_ss<1>(d, tA + ((UM + 9) % 5) * 512 + ks * 2, db);
            }
        }
        wgmma_commit();
    };
    bar_sync<256>(2 + wg);
    piece(pa, IC<0>{});
    bar_arrive<256>(3 + wg);
    if (wg == 1) store_pk(10, 14);
    wgmma_wait<0>();
#pragma unroll
    for (int ks = 0; ks < 4; ks++) af[16 + ks] = ldmatrix_x4((alane ^ (ks * 32)) + ((UM + 9) % 5) * 8192);
    optr += 64 * N_ * 2;
    store_cols(pa, optr);
    bar_sync<256>(4 + wg);
    piece(pb, IC<4>{});
    bar_arrive<256>(5 + wg);
    wgmma_wait<0>();
    store_cols(pb, optr + 4 * 64);
    bar_sync<256>(6 + wg);
    piece(pc, IC<6>{});
    if (wg == 0) bar_arrive<256>(7);
    cluster_arrive();
    wgmma_wait<0>();
    store_cols(pc, optr + 6 * 64);
    cluster_wait();
}

typedef CUresult (*EncodeFn)(CUtensorMap*, CUtensorMapDataType, cuuint32_t, void*, const cuuint64_t*, const cuuint64_t*,
                             const cuuint32_t*, const cuuint32_t*, CUtensorMapInterleave, CUtensorMapSwizzle,
                             CUtensorMapL2promotion, CUtensorMapFloatOOBfill);

extern "C" void kernel_launch(void* const* d_in, const int* in_sizes, int n_in, void* d_out, int out_size) {
    static EncodeFn encode = nullptr;
    static void *wimg = nullptr, *gflags = nullptr;
    if (!encode) {
        cudaGetSymbolAddress(&wimg, g_wimg);
        cudaGetSymbolAddress(&gflags, g_flag);
        void* fn = nullptr;
        cudaDriverEntryPointQueryResult qr;
        cudaGetDriverEntryPoint("cuTensorMapEncodeTiled", &fn, cudaEnableDefault, &qr);
        encode = (EncodeFn)fn;
        cudaFuncSetAttribute(nf4_gemm_kernel, cudaFuncAttributeMaxDynamicSharedMemorySize, SMEM_BYTES);
    }
    void *x = d_in[0], *qw = d_in[1], *cb = d_in[2], *absmax = d_in[3];
    auto map = [&](CUtensorMapDataType t, int rank, void* p, const cuuint64_t* dims, const cuuint64_t* strides, const cuuint32_t* box, bool swizzle) {
        CUtensorMap m;
        const cuuint32_t es[3] = {1, 1, 1};
        encode(&m, t, rank, p, dims, strides, box, es, CU_TENSOR_MAP_INTERLEAVE_NONE,
               swizzle ? CU_TENSOR_MAP_SWIZZLE_128B : CU_TENSOR_MAP_SWIZZLE_NONE,
               swizzle ? CU_TENSOR_MAP_L2_PROMOTION_L2_128B : CU_TENSOR_MAP_L2_PROMOTION_NONE, CU_TENSOR_MAP_FLOAT_OOB_FILL_NONE);
        return m;
    };
    const cuuint64_t xd[2] = {K_, M_}, xs[1] = {K_ * 2};
    const cuuint64_t q3d[3] = {32, K_, N_ / 32}, q3s[2] = {N_ * 4, 128};
    const cuuint64_t q2d[2] = {N_, K_}, q2s[1] = {N_ * 4};
    const cuuint64_t sd[2] = {N_, KC}, ss[1] = {N_ * 2};
    const cuuint32_t bx[2] = {BK, 16}, bx64[2] = {BK, 64}, bq16[3] = {32, 16, 7}, bq8[3] = {32, 8, 7}, bq1[2] = {32, 8}, bs[2] = {BN, KC - 2};
    nf4_gemm_kernel<<<128, 256, SMEM_BYTES>>>(
        (const uint8_t*)qw, (const __nv_bfloat16*)cb, (const __nv_bfloat16*)absmax, (uint8_t*)wimg, (unsigned*)gflags, (uint8_t*)d_out, 0u,
        map(CU_TENSOR_MAP_DATA_TYPE_BFLOAT16, 2, x, xd, xs, bx, true), map(CU_TENSOR_MAP_DATA_TYPE_BFLOAT16, 2, x, xd, xs, bx64, true),
        map(CU_TENSOR_MAP_DATA_TYPE_INT32, 3, qw, q3d, q3s, bq16, true), map(CU_TENSOR_MAP_DATA_TYPE_INT32, 3, qw, q3d, q3s, bq8, true),
        map(CU_TENSOR_MAP_DATA_TYPE_INT32, 2, qw, q2d, q2s, bq1, true), map(CU_TENSOR_MAP_DATA_TYPE_BFLOAT16, 2, absmax, sd, ss, bs, false));
}
```

```cpp
#include <cuda_runtime.h>
#include <cuda_bf16.h>
#include <cuda.h>
#include <stdint.h>

constexpr int M_ = 2048, K_ = 1024, N_ = 3584;
constexpr int BM = 256, BN = 224, BK = 64;
constexpr int KC = K_ / BK;

__device__ __forceinline__ uint32_t smem_u32(const void* p) { return (uint32_t)__cvta_generic_to_shared(p); }
__device__ __forceinline__ bool elect() {
    uint32_t ok;
    asm volatile("{\n.reg .pred p;\nelect.sync _|p, 0xffffffff;\nselp.u32 %0, 1, 0, p;\n}\n" : "=r"(ok));
    return ok != 0;
}
template <int I> struct IC { static constexpr int value = I; };
template <int I, int N, class F> __device__ __forceinline__ void static_for(F&& f) {
    if constexpr (I < N) { f(IC<I>{}); static_for<I + 1, N>(f); }
}

__device__ __forceinline__ void mbar_init(uint32_t bar, uint32_t cnt) { asm volatile("mbarrier.init.shared::cta.b64 [%0], %1;" ::"r"(bar), "r"(cnt) : "memory"); }
__device__ __forceinline__ void mbar_init_fence() { asm volatile("fence.mbarrier_init.release.cluster;" ::: "memory"); }
__device__ __forceinline__ void mbar_expect_tx(uint32_t bar, uint32_t bytes) { asm volatile("mbarrier.arrive.expect_tx.shared::cta.b64 _, [%0], %1;" ::"r"(bar), "r"(bytes) : "memory"); }
__device__ __forceinline__ void mbar_arrive(uint32_t bar) { asm volatile("mbarrier.arrive.shared::cta.b64 _, [%0];" ::"r"(bar) : "memory"); }
__device__ __forceinline__ void mbar_arrive_n(uint32_t bar, uint32_t n) { asm volatile("mbarrier.arrive.shared::cta.b64 _, [%0], %1;" ::"r"(bar), "r"(n) : "memory"); }
__device__ __forceinline__ void mbar_arrive_both(uint32_t bar) {
    asm volatile("{\n.reg .b32 ra;\nmapa.shared::cluster.u32 ra, %0, 0;\nmbarrier.arrive.shared::cluster.b64 _, [ra];\n"
                 "mapa.shared::cluster.u32 ra, %0, 1;\nmbarrier.arrive.shared::cluster.b64 _, [ra];\n}\n" ::"r"(bar) : "memory");
}
#define MBAR_TRY(p, b, q) "mbarrier.try_wait.parity.shared::cta.b64 " p ", [" b "], " q ";\n"
#define MBAR_WAIT(TRY) \
    "{\n.reg .pred p0, p1, p2;\n.reg .b32 n;\n" TRY "@p0 bra LAB_DONE;\nmov.b32 n, 0;\nLAB_WAIT:\n" TRY \
    "@p0 bra LAB_DONE;\nadd.u32 n, n, 1;\nsetp.lt.u32 p0, n, 0x40000;\n@p0 bra LAB_WAIT;\ntrap;\nLAB_DONE:\n}\n"
__device__ __forceinline__ void mbar_wait(uint32_t b0, uint32_t q0) {
    asm volatile(MBAR_WAIT(MBAR_TRY("p0", "%0", "%1")) ::"r"(b0), "r"(q0) : "memory");
}
__device__ __forceinline__ void mbar_wait2(uint32_t b0, uint32_t q0, uint32_t b1, uint32_t q1) {
    asm volatile(MBAR_WAIT(MBAR_TRY("p0", "%0", "%1") MBAR_TRY("p1", "%2", "%3") "and.pred p0, p0, p1;\n")
                 ::"r"(b0), "r"(q0), "r"(b1), "r"(q1) : "memory");
}
__device__ __forceinline__ void mbar_wait3(uint32_t b0, uint32_t q0, uint32_t b1, uint32_t q1, uint32_t b2, uint32_t q2) {
    asm volatile(MBAR_WAIT(MBAR_TRY("p0", "%0", "%1") MBAR_TRY("p1", "%2", "%3") MBAR_TRY("p2", "%4", "%5") "and.pred p0, p0, p1;\nand.pred p0, p0, p2;\n")
                 ::"r"(b0), "r"(q0), "r"(b1), "r"(q1), "r"(b2), "r"(q2) : "memory");
}
__device__ __forceinline__ void cluster_arrive() { asm volatile("barrier.cluster.arrive.relaxed.aligned;" ::: "memory"); }
__device__ __forceinline__ void cluster_wait() { asm volatile("barrier.cluster.wait.acquire.aligned;" ::: "memory"); }
template <int NTHR> __device__ __forceinline__ void bar_arrive(int id) { asm volatile("bar.arrive %0, %1;" ::"r"(id), "n"(NTHR) : "memory"); }
template <int NTHR> __device__ __forceinline__ void bar_sync(int id) { asm volatile("bar.sync %0, %1;" ::"r"(id), "n"(NTHR) : "memory"); }
__device__ __forceinline__ void delay(unsigned clks) {
    asm volatile(
        "{\n.reg .pred p;\n.reg .b32 t0, t;\n"
        "mov.u32 t0, %%clock;\n"
        "LAB_DELAY:\n"
        "mov.u32 t, %%clock;\n"
        "sub.u32 t, t, t0;\n"
        "setp.lt.u32 p, t, %0;\n"
        "vote.sync.any.pred p, p, 0xffffffff;\n"
        "@p bra.uni LAB_DELAY;\n}\n" ::"r"(clks) : "memory");
}

__device__ __forceinline__ void tma_load_2d(uint32_t dst, const CUtensorMap* tm, int c0, int c1, uint32_t bar) {
    asm volatile("cp.async.bulk.tensor.2d.shared::cluster.global.mbarrier::complete_tx::bytes [%0], [%1, {%2, %3}], [%4];"
                 ::"r"(dst), "l"(tm), "r"(c0), "r"(c1), "r"(bar) : "memory");
}
__device__ __forceinline__ void tma_load_3d(uint32_t dst, const CUtensorMap* tm, int c0, int c1, int c2, uint32_t bar) {
    asm volatile("cp.async.bulk.tensor.3d.shared::cluster.global.mbarrier::complete_tx::bytes [%0], [%1, {%2, %3, %4}], [%5];"
                 ::"r"(dst), "l"(tm), "r"(c0), "r"(c1), "r"(c2), "r"(bar) : "memory");
}
__device__ __forceinline__ void bulk_load_mc(uint32_t dst, const void* src, uint32_t bytes, uint32_t bar) {
    asm volatile("cp.async.bulk.shared::cluster.global.mbarrier::complete_tx::bytes.multicast::cluster [%0], [%1], %2, [%3], %4;"
                 ::"r"(dst), "l"(src), "r"(bytes), "r"(bar), "h"((uint16_t)3) : "memory");
}
__device__ __forceinline__ uint32_t mapa(uint32_t addr, uint32_t cta) {
    uint32_t r; asm("mapa.shared::cluster.u32 %0, %1, %2;" : "=r"(r) : "r"(addr), "r"(cta)); return r;
}
__device__ __forceinline__ void copy_to_peer(uint32_t addr, uint32_t bytes, uint32_t bar, uint32_t peer) {
    asm volatile("cp.async.bulk.shared::cluster.shared::cta.mbarrier::complete_tx::bytes [%0], [%1], %2, [%3];"
                 ::"r"(mapa(addr, peer)), "r"(addr), "r"(bytes), "r"(mapa(bar, peer)) : "memory");
}
__device__ __forceinline__ void fence_async_smem() { asm volatile("fence.proxy.async.shared::cta;" ::: "memory"); }

__device__ __forceinline__ uint4 lds128(uint32_t a) {
    uint4 v; asm volatile("ld.shared.v4.b32 {%0, %1, %2, %3}, [%4];" : "=r"(v.x), "=r"(v.y), "=r"(v.z), "=r"(v.w) : "r"(a) : "memory"); return v;
}
__device__ __forceinline__ uint32_t lds32(uint32_t a) {
    uint32_t v; asm volatile("ld.shared.b32 %0, [%1];" : "=r"(v) : "r"(a) : "memory"); return v;
}
__device__ __forceinline__ uint4 ldmatrix_x4(uint32_t a) {
    uint4 v;
    asm volatile("ldmatrix.sync.aligned.m8n8.x4.shared.b16 {%0, %1, %2, %3}, [%4];" : "=r"(v.x), "=r"(v.y), "=r"(v.z), "=r"(v.w) : "r"(a) : "memory");
    return v;
}
__device__ __forceinline__ void sts32(uint32_t a, uint32_t v) { asm volatile("st.shared.b32 [%0], %1;" ::"r"(a), "r"(v) : "memory"); }
__device__ __forceinline__ void stg32(void* p, uint32_t v) { asm volatile("st.global.b32 [%0], %1;" ::"l"(p), "r"(v) : "memory"); }
__device__ __forceinline__ void stg128(void* p, uint32_t a, uint32_t b, uint32_t c, uint32_t d) {
    asm volatile("st.global.v4.b32 [%0], {%1, %2, %3, %4};" ::"l"(p), "r"(a), "r"(b), "r"(c), "r"(d) : "memory");
}

__device__ __forceinline__ unsigned ld_relaxed(const void* p) {
    unsigned v; asm volatile("ld.relaxed.gpu.global.u32 %0, [%1];" : "=r"(v) : "l"(p) : "memory"); return v;
}
__device__ __forceinline__ void read_l2(uint32_t dst, const void* src, uint32_t on) {
    asm volatile("{\n.reg .pred p;\nsetp.ne.u32 p, %2, 0;\n@p cp.async.cg.shared.global [%0], [%1], 16;\n}\ncp.async.commit_group;" ::"r"(dst), "l"(src), "r"(on) : "memory");
}
template <int N> __device__ __forceinline__ void read_wait() { asm volatile("cp.async.wait_group %0;" ::"n"(N) : "memory"); __syncwarp(); }
__device__ __forceinline__ void read_arrive(uint32_t bar) { asm volatile("cp.async.mbarrier.arrive.noinc.shared::cta.b64 [%0];" ::"r"(bar) : "memory"); }
__device__ __forceinline__ unsigned after(unsigned n, unsigned p, unsigned z) {
    unsigned r; asm volatile("lop3.b32 %0, %1, %2, %3, 0xea;" : "=r"(r) : "r"(p), "r"(z), "r"(n)); return r;
}
__device__ __forceinline__ void red_add(unsigned* f, unsigned n) { asm volatile("red.relaxed.gpu.global.add.u32 [%0], %1;" ::"l"(f), "r"(n) : "memory"); }
__device__ __forceinline__ void poll_ge(const unsigned* f, unsigned v, unsigned ready) {
    asm volatile(
        "{\n.reg .pred p;\n.reg .b32 v, n;\n"
        "setp.lt.u32 p, %1, %2;\n"
        "vote.sync.any.pred p, p, 0xffffffff;\n"
        "@!p bra.uni LAB_DONE;\n"
        "mov.b32 n, 0;\n"
        "LAB_POLL:\n"
        "ld.relaxed.gpu.global.u32 v, [%0];\n"
        "setp.lt.u32 p, v, %2;\n"
        "vote.sync.any.pred p, p, 0xffffffff;\n"
        "@!p bra.uni LAB_DONE;\n"
        "add.u32 n, n, 1;\n"
        "setp.lt.u32 p, n, 0x400000;\n"
        "@p bra.uni LAB_POLL;\n"
        "LAB_DONE:\n}\n" ::"l"(f), "r"(v), "r"(ready) : "memory");
}

__device__ __forceinline__ uint32_t pack_bf16(float lo, float hi) {
    uint32_t r; asm("cvt.rn.bf16x2.f32 %0, %1, %2;" : "=r"(r) : "f"(hi), "f"(lo)); return r;
}
__device__ __forceinline__ uint32_t mul_bf16x2(uint32_t a, uint32_t b) { uint32_t r; asm("mul.rn.bf16x2 %0, %1, %2;" : "=r"(r) : "r"(a), "r"(b)); return r; }
__device__ __forceinline__ uint32_t prmt(uint32_t a, uint32_t b, uint32_t s) { uint32_t r; asm("prmt.b32 %0, %1, %2, %3;" : "=r"(r) : "r"(a), "r"(b), "r"(s)); return r; }
__device__ __forceinline__ uint32_t madi(uint32_t hi, uint32_t m, uint32_t lo) { uint32_t r; asm("mad.lo.u32 %0, %1, %2, %3;" : "=r"(r) : "r"(hi), "r"(m), "r"(lo)); return r; }
__device__ __forceinline__ uint32_t pack8(const uint4& a, const uint4& b) {
    return madi(madi(madi(b.w, 65536, a.w), 16, madi(b.z, 65536, a.z)), 256, madi(madi(b.y, 65536, a.y), 16, madi(b.x, 65536, a.x)));
}
struct Lut { uint32_t lo[4], hi[4]; };
__device__ __forceinline__ void lookup4(uint32_t s7, uint32_t sel, const Lut& t, uint32_t& w01, uint32_t& w23) {
    const uint32_t lo = prmt(prmt(t.lo[0], t.lo[1], s7), prmt(t.lo[2], t.lo[3], s7), sel);
    const uint32_t hi = prmt(prmt(t.hi[0], t.hi[1], s7), prmt(t.hi[2], t.hi[3], s7), sel);
    w01 = prmt(lo, hi, 0x5140);
    w23 = prmt(lo, hi, 0x7362);
}
__device__ __forceinline__ uint4 dequant8(uint32_t p, const uint4& sc, const Lut& t) {
    const uint32_t m8 = p & 0x88888888u, s7 = p & 0x77777777u;
    uint4 r;
    lookup4(s7, (m8 >> 1) + 0x3210u, t, r.x, r.y);
    lookup4(s7 >> 16, (m8 >> 17) + 0x3210u, t, r.z, r.w);
    r.x = mul_bf16x2(r.x, sc.x); r.y = mul_bf16x2(r.y, sc.y); r.z = mul_bf16x2(r.z, sc.z); r.w = mul_bf16x2(r.w, sc.w);
    return r;
}
__device__ __forceinline__ uint4 dequant8_shfl(const uint4& q0, const uint4& q1, const uint4& sc, uint32_t tab) {
    uint4 r;
    r.x = mul_bf16x2(__byte_perm(__shfl_sync(~0u, tab, q0.x), __shfl_sync(~0u, tab, q0.y), 0x5410), sc.x);
    r.y = mul_bf16x2(__byte_perm(__shfl_sync(~0u, tab, q0.z), __shfl_sync(~0u, tab, q0.w), 0x5410), sc.y);
    r.z = mul_bf16x2(__byte_perm(__shfl_sync(~0u, tab, q1.x), __shfl_sync(~0u, tab, q1.y), 0x5410), sc.z);
    r.w = mul_bf16x2(__byte_perm(__shfl_sync(~0u, tab, q1.z), __shfl_sync(~0u, tab, q1.w), 0x5410), sc.w);
    return r;
}

__device__ __forceinline__ void wgmma_fence() { asm volatile("wgmma.fence.sync.aligned;" ::: "memory"); }
__device__ __forceinline__ void wgmma_commit() { asm volatile("wgmma.commit_group.sync.aligned;" ::: "memory"); }
template <int N> __device__ __forceinline__ void wgmma_wait() { asm volatile("wgmma.wait_group.sync.aligned %0;" ::"n"(N) : "memory"); }
template <int SCALE_D>
__device__ __forceinline__ void wgmma_ss(float (&d)[112], uint32_t descA, uint32_t descB) {
    asm volatile(
        "{\n.reg .pred p;\n.reg .b64 da, db;\nsetp.ne.b32 p, %114, 0;\n"
        "mov.b64 da, {%112, 0x40000040};\nmov.b64 db, {%113, 0x10};\n"
        "wgmma.mma_async.sync.aligned.m64n224k16.f32.bf16.bf16 "
        "{%0, %1, %2, %3, %4, %5, %6, %7, %8, %9, %10, %11, %12, %13, %14, %15, "
        "%16, %17, %18, %19, %20, %21, %22, %23, %24, %25, %26, %27, %28, %29, %30, %31, "
        "%32, %33, %34, %35, %36, %37, %38, %39, %40, %41, %42, %43, %44, %45, %46, %47, "
        "%48, %49, %50, %51, %52, %53, %54, %55, %56, %57, %58, %59, %60, %61, %62, %63, "
        "%64, %65, %66, %67, %68, %69, %70, %71, %72, %73, %74, %75, %76, %77, %78, %79, "
        "%80, %81, %82, %83, %84, %85, %86, %87, %88, %89, %90, %91, %92, %93, %94, %95, "
        "%96, %97, %98, %99, %100, %101, %102, %103, %104, %105, %106, %107, %108, %109, %110, %111}, "
        "da, db, p, 1, 1, 0, 1;\n}\n"
        : "+f"(d[0]), "+f"(d[1]), "+f"(d[2]), "+f"(d[3]), "+f"(d[4]), "+f"(d[5]), "+f"(d[6]), "+f"(d[7]),
          "+f"(d[8]), "+f"(d[9]), "+f"(d[10]), "+f"(d[11]), "+f"(d[12]), "+f"(d[13]), "+f"(d[14]), "+f"(d[15]),
          "+f"(d[16]), "+f"(d[17]), "+f"(d[18]), "+f"(d[19]), "+f"(d[20]), "+f"(d[21]), "+f"(d[22]), "+f"(d[23]),
          "+f"(d[24]), "+f"(d[25]), "+f"(d[26]), "+f"(d[27]), "+f"(d[28]), "+f"(d[29]), "+f"(d[30]), "+f"(d[31]),
          "+f"(d[32]), "+f"(d[33]), "+f"(d[34]), "+f"(d[35]), "+f"(d[36]), "+f"(d[37]), "+f"(d[38]), "+f"(d[39]),
          "+f"(d[40]), "+f"(d[41]), "+f"(d[42]), "+f"(d[43]), "+f"(d[44]), "+f"(d[45]), "+f"(d[46]), "+f"(d[47]),
          "+f"(d[48]), "+f"(d[49]), "+f"(d[50]), "+f"(d[51]), "+f"(d[52]), "+f"(d[53]), "+f"(d[54]), "+f"(d[55]),
          "+f"(d[56]), "+f"(d[57]), "+f"(d[58]), "+f"(d[59]), "+f"(d[60]), "+f"(d[61]), "+f"(d[62]), "+f"(d[63]),
          "+f"(d[64]), "+f"(d[65]), "+f"(d[66]), "+f"(d[67]), "+f"(d[68]), "+f"(d[69]), "+f"(d[70]), "+f"(d[71]),
          "+f"(d[72]), "+f"(d[73]), "+f"(d[74]), "+f"(d[75]), "+f"(d[76]), "+f"(d[77]), "+f"(d[78]), "+f"(d[79]),
          "+f"(d[80]), "+f"(d[81]), "+f"(d[82]), "+f"(d[83]), "+f"(d[84]), "+f"(d[85]), "+f"(d[86]), "+f"(d[87]),
          "+f"(d[88]), "+f"(d[89]), "+f"(d[90]), "+f"(d[91]), "+f"(d[92]), "+f"(d[93]), "+f"(d[94]), "+f"(d[95]),
          "+f"(d[96]), "+f"(d[97]), "+f"(d[98]), "+f"(d[99]), "+f"(d[100]), "+f"(d[101]), "+f"(d[102]), "+f"(d[103]),
          "+f"(d[104]), "+f"(d[105]), "+f"(d[106]), "+f"(d[107]), "+f"(d[108]), "+f"(d[109]), "+f"(d[110]), "+f"(d[111])
        : "r"(descA), "r"(descB), "n"(SCALE_D));
}

template <int SCALE_D>
__device__ __forceinline__ void wgmma_ss(float (&d)[64], uint32_t descA, uint32_t descB) {
    asm volatile(
        "{\n.reg .pred p;\n.reg .b64 da, db;\nsetp.ne.b32 p, %66, 0;\n"
        "mov.b64 da, {%64, 0x40000040};\nmov.b64 db, {%65, 0x10};\n"
        "wgmma.mma_async.sync.aligned.m64n128k16.f32.bf16.bf16 "
        "{%0, %1, %2, %3, %4, %5, %6, %7, %8, %9, %10, %11, %12, %13, %14, %15, "
        "%16, %17, %18, %19, %20, %21, %22, %23, %24, %25, %26, %27, %28, %29, %30, %31, "
        "%32, %33, %34, %35, %36, %37, %38, %39, %40, %41, %42, %43, %44, %45, %46, %47, "
        "%48, %49, %50, %51, %52, %53, %54, %55, %56, %57, %58, %59, %60, %61, %62, %63}, "
        "da, db, p, 1, 1, 0, 1;\n}\n"
        : "+f"(d[0]), "+f"(d[1]), "+f"(d[2]), "+f"(d[3]), "+f"(d[4]), "+f"(d[5]), "+f"(d[6]), "+f"(d[7]),
          "+f"(d[8]), "+f"(d[9]), "+f"(d[10]), "+f"(d[11]), "+f"(d[12]), "+f"(d[13]), "+f"(d[14]), "+f"(d[15]),
          "+f"(d[16]), "+f"(d[17]), "+f"(d[18]), "+f"(d[19]), "+f"(d[20]), "+f"(d[21]), "+f"(d[22]), "+f"(d[23]),
          "+f"(d[24]), "+f"(d[25]), "+f"(d[26]), "+f"(d[27]), "+f"(d[28]), "+f"(d[29]), "+f"(d[30]), "+f"(d[31]),
          "+f"(d[32]), "+f"(d[33]), "+f"(d[34]), "+f"(d[35]), "+f"(d[36]), "+f"(d[37]), "+f"(d[38]), "+f"(d[39]),
          "+f"(d[40]), "+f"(d[41]), "+f"(d[42]), "+f"(d[43]), "+f"(d[44]), "+f"(d[45]), "+f"(d[46]), "+f"(d[47]),
          "+f"(d[48]), "+f"(d[49]), "+f"(d[50]), "+f"(d[51]), "+f"(d[52]), "+f"(d[53]), "+f"(d[54]), "+f"(d[55]),
          "+f"(d[56]), "+f"(d[57]), "+f"(d[58]), "+f"(d[59]), "+f"(d[60]), "+f"(d[61]), "+f"(d[62]), "+f"(d[63])
        : "r"(descA), "r"(descB), "n"(SCALE_D));
}

__device__ __forceinline__ void wgmma_rs(float (&d)[64], const uint4& a, uint32_t descB) {
    asm volatile(
        "{\n.reg .pred p;\n.reg .b64 db;\nsetp.eq.b32 p, 0, 0;\n"
        "mov.b64 db, {%68, 0x10};\n"
        "wgmma.mma_async.sync.aligned.m64n128k16.f32.bf16.bf16 "
        "{%0, %1, %2, %3, %4, %5, %6, %7, %8, %9, %10, %11, %12, %13, %14, %15, "
        "%16, %17, %18, %19, %20, %21, %22, %23, %24, %25, %26, %27, %28, %29, %30, %31, "
        "%32, %33, %34, %35, %36, %37, %38, %39, %40, %41, %42, %43, %44, %45, %46, %47, "
        "%48, %49, %50, %51, %52, %53, %54, %55, %56, %57, %58, %59, %60, %61, %62, %63}, "
        "{%64, %65, %66, %67}, db, p, 1, 1, 1;\n}\n"
        : "+f"(d[0]), "+f"(d[1]), "+f"(d[2]), "+f"(d[3]), "+f"(d[4]), "+f"(d[5]), "+f"(d[6]), "+f"(d[7]),
          "+f"(d[8]), "+f"(d[9]), "+f"(d[10]), "+f"(d[11]), "+f"(d[12]), "+f"(d[13]), "+f"(d[14]), "+f"(d[15]),
          "+f"(d[16]), "+f"(d[17]), "+f"(d[18]), "+f"(d[19]), "+f"(d[20]), "+f"(d[21]), "+f"(d[22]), "+f"(d[23]),
          "+f"(d[24]), "+f"(d[25]), "+f"(d[26]), "+f"(d[27]), "+f"(d[28]), "+f"(d[29]), "+f"(d[30]), "+f"(d[31]),
          "+f"(d[32]), "+f"(d[33]), "+f"(d[34]), "+f"(d[35]), "+f"(d[36]), "+f"(d[37]), "+f"(d[38]), "+f"(d[39]),
          "+f"(d[40]), "+f"(d[41]), "+f"(d[42]), "+f"(d[43]), "+f"(d[44]), "+f"(d[45]), "+f"(d[46]), "+f"(d[47]),
          "+f"(d[48]), "+f"(d[49]), "+f"(d[50]), "+f"(d[51]), "+f"(d[52]), "+f"(d[53]), "+f"(d[54]), "+f"(d[55]),
          "+f"(d[56]), "+f"(d[57]), "+f"(d[58]), "+f"(d[59]), "+f"(d[60]), "+f"(d[61]), "+f"(d[62]), "+f"(d[63])
        : "r"(a.x), "r"(a.y), "r"(a.z), "r"(a.w), "r"(descB));
}

__device__ __forceinline__ void wgmma_rs(float (&d)[32], const uint4& a, uint32_t descB) {
    asm volatile(
        "{\n.reg .pred p;\n.reg .b64 db;\nsetp.eq.b32 p, 0, 0;\n"
        "mov.b64 db, {%36, 0x10};\n"
        "wgmma.mma_async.sync.aligned.m64n64k16.f32.bf16.bf16 "
        "{%0, %1, %2, %3, %4, %5, %6, %7, %8, %9, %10, %11, %12, %13, %14, %15, "
        "%16, %17, %18, %19, %20, %21, %22, %23, %24, %25, %26, %27, %28, %29, %30, %31}, "
        "{%32, %33, %34, %35}, db, p, 1, 1, 1;\n}\n"
        : "+f"(d[0]), "+f"(d[1]), "+f"(d[2]), "+f"(d[3]), "+f"(d[4]), "+f"(d[5]), "+f"(d[6]), "+f"(d[7]),
          "+f"(d[8]), "+f"(d[9]), "+f"(d[10]), "+f"(d[11]), "+f"(d[12]), "+f"(d[13]), "+f"(d[14]), "+f"(d[15]),
          "+f"(d[16]), "+f"(d[17]), "+f"(d[18]), "+f"(d[19]), "+f"(d[20]), "+f"(d[21]), "+f"(d[22]), "+f"(d[23]),
          "+f"(d[24]), "+f"(d[25]), "+f"(d[26]), "+f"(d[27]), "+f"(d[28]), "+f"(d[29]), "+f"(d[30]), "+f"(d[31])
        : "r"(a.x), "r"(a.y), "r"(a.z), "r"(a.w), "r"(descB));
}

__device__ __forceinline__ void wgmma_rs(float (&d)[16], const uint4& a, uint32_t descB) {
    asm volatile(
        "{\n.reg .pred p;\n.reg .b64 db;\nsetp.eq.b32 p, 0, 0;\n"
        "mov.b64 db, {%20, 0x10};\n"
        "wgmma.mma_async.sync.aligned.m64n32k16.f32.bf16.bf16 "
        "{%0, %1, %2, %3, %4, %5, %6, %7, %8, %9, %10, %11, %12, %13, %14, %15}, "
        "{%16, %17, %18, %19}, db, p, 1, 1, 1;\n}\n"
        : "+f"(d[0]), "+f"(d[1]), "+f"(d[2]), "+f"(d[3]), "+f"(d[4]), "+f"(d[5]), "+f"(d[6]), "+f"(d[7]),
          "+f"(d[8]), "+f"(d[9]), "+f"(d[10]), "+f"(d[11]), "+f"(d[12]), "+f"(d[13]), "+f"(d[14]), "+f"(d[15])
        : "r"(a.x), "r"(a.y), "r"(a.z), "r"(a.w), "r"(descB));
}

constexpr int NT = N_ / BN, MT = M_ / BM;
constexpr int W_BYTES = BN * BK * 2;
constexpr int SLAB = 8 * BN * 4;
constexpr int SC_ROW = BN * 2;
constexpr int X_OFF = 0;
constexpr int W_OFF = 10 * 8192;
constexpr int R_OFF = W_OFF + 4 * W_BYTES;
constexpr int SC_OFF = R_OFF + W_BYTES - 2 * SC_ROW;
constexpr int RAW0_OFF = W_OFF + 2 * W_BYTES;
constexpr int BAR_OFF = SC_OFF + 16 * SC_ROW;
constexpr int SMEM_BYTES = BAR_OFF + 896;
constexpr unsigned READY = MT * 7;
constexpr int UM = 22;
constexpr int NAG = 7;

__device__ __align__(1024) uint8_t g_wimg[(size_t)NT * KC * W_BYTES];
__device__ unsigned g_flag[NT * 32];

__host__ __device__ constexpr int slab_at(int u) { return u == 0 ? 2 : u == 1 ? 3 : u == 3 ? 4 : u == 5 ? 5 : (u >= 7 && u <= 16) ? u - 1 : -1; }
__host__ __device__ constexpr int wload_at(int u) {
    return u <= 10 ? ((u & 1) ? -1 : u / 2 + 1) : u <= 17 ? ((u & 1) ? (u + 3) / 2 : -1) : u == 18 ? 11 : u == 19 ? 12 : u == 20 ? 15 : u == 21 ? 13 : -1;
}
__host__ __device__ constexpr int tail_chunk(int j) { return j == 3 ? 15 : j == 4 ? 14 : 11 + j; }
__host__ __device__ constexpr int wbuf(int c) { return c == 15 ? 4 : c & 3; }

template <int NR>
__device__ __forceinline__ void store_cols(const float (&acc)[NR], uint8_t* p) {
#pragma unroll
    for (int j = 0; j < NR / 16; j++) {
        const int i = 16 * j;
        stg128(p + j * 64, pack_bf16(acc[i], acc[i + 1]), pack_bf16(acc[i + 4], acc[i + 5]), pack_bf16(acc[i + 8], acc[i + 9]), pack_bf16(acc[i + 12], acc[i + 13]));
        stg128(p + j * 64 + 8 * N_ * 2, pack_bf16(acc[i + 2], acc[i + 3]), pack_bf16(acc[i + 6], acc[i + 7]), pack_bf16(acc[i + 10], acc[i + 11]), pack_bf16(acc[i + 14], acc[i + 15]));
    }
}

__global__ void __cluster_dims__(2, 1, 1) __launch_bounds__(256, 1)
nf4_gemm_kernel(const uint8_t* __restrict__ qw, const __nv_bfloat16* __restrict__ cb, const __nv_bfloat16* __restrict__ absmax,
                uint8_t* __restrict__ wimg, unsigned* __restrict__ gflags, uint8_t* __restrict__ out, const unsigned zero,
                const __grid_constant__ CUtensorMap tmx, const __grid_constant__ CUtensorMap tmx64, const __grid_constant__ CUtensorMap tmq16,
                const __grid_constant__ CUtensorMap tmq8, const __grid_constant__ CUtensorMap tmq1, const __grid_constant__ CUtensorMap tms) {
    extern __shared__ __align__(1024) uint8_t smem[];
    const int rank = blockIdx.x & 1;
    const int mt = (blockIdx.x & 3) + (blockIdx.x >> 6) * 4, nt = (blockIdx.x >> 2) & 15;
    const uint8_t* share;
    uint4 s1a, s1b;
    asm volatile(
        "{\n.reg .b32 t, b, o, h;\n.reg .b64 a;\n.reg .pred p;\n"
        "mov.u32 t, %%tid.x;\nmov.u32 b, %%ctaid.x;\n"
        "shl.b32 o, t, 4;\nshr.u32 h, t, 3;\nmad.lo.u32 o, h, %10 - 128, o;\n"
        "shr.u32 h, t, 5;\nmad.lo.u32 o, h, 128 - 4 * %10, o;\n"
        "and.b32 h, b, 3;\nmad.lo.u32 o, h, 8 * %10 - %11 / 4, o;\n"
        "shr.u32 h, b, 6;\nmad.lo.u32 o, h, 32 * %10 - 16 * %11, o;\n"
        "mad.lo.u32 o, b, %11 / 4, o;\n"
        "cvt.u64.u32 a, o;\nadd.u64 a, a, %9;\n"
        "ld.global.L1::no_allocate.v4.u32 {%1, %2, %3, %4}, [a + 64 * %10];\n"
        "ld.global.L1::no_allocate.v4.u32 {%5, %6, %7, %8}, [a + 68 * %10];\n"
        "setp.lt.u32 p, b, 64;\n@p prefetch.global.L2 [a + 96 * %10];\n@p prefetch.global.L2 [a + 100 * %10];\n"
        "mov.b64 %0, a;\n}\n"
        : "=l"(share), "=r"(s1a.x), "=r"(s1a.y), "=r"(s1a.z), "=r"(s1a.w), "=r"(s1b.x), "=r"(s1b.y), "=r"(s1b.z), "=r"(s1b.w)
        : "l"(qw), "n"(N_ * 4), "n"(BN * 4) : "memory");
    const uint32_t sbase = smem_u32(smem);
    const int warp = __shfl_sync(~0u, (int)(threadIdx.x >> 5), 0);
    const int wg = warp >> 2, wj = warp & 3;
    const int lane = threadIdx.x & 31;
    const uint32_t bars = sbase + BAR_OFF;
    const uint32_t snap = bars;
    const uint32_t xfull = bars + 64 + wg * 40;
    const uint32_t wfull = bars + 144;
    const uint32_t wempty = bars + 184;
    const uint32_t ringfull = bars + 216;
    const uint32_t rawbar = bars + 248;
    const uint32_t wown = bars + 264;
    const uint32_t stored = bars + 272 - 8;
    const uint32_t wlast = bars + 344;
    const uint32_t xbase = sbase + X_OFF + wg * 40960, wbase = sbase + W_OFF, rbase = sbase + R_OFF;
    const int xrow = mt * BM + wg * 128 + wj * 16;
    const uint8_t* wsrc = wimg + (size_t)nt * KC * W_BYTES;
    unsigned* flags = gflags + nt * 32;

    auto load_x = [&](int u, int cs = -1) {
        const int c = u < UM ? u >> 1 : tail_chunk((u - UM) % 5), b = u < UM ? u & 1 : (u - UM) / 5;
        mbar_expect_tx(xfull + 8 * (u % 5), cs >= 0 ? 3072 : 2048);
        tma_load_2d(xbase + (u % 5) * 8192 + wj * 2048, &tmx, c * BK, xrow + b * 64, xfull + 8 * (u % 5));
        if (cs >= 0) tma_load_2d(rbase + (cs & 3) * SLAB + warp * 1024, &tmq1, nt * BN + warp * 32, cs * BK + mt * 8, xfull + 8 * (u % 5));
    };
    auto load_x64 = [&](int g, int u) {
        const uint32_t bar = bars + 64 + g * 40 + 8 * u;
        mbar_arrive_n(bar, 3);
        mbar_expect_tx(bar, 8192);
        tma_load_2d(sbase + X_OFF + g * 40960 + u * 8192, &tmx64, (u >> 1) * BK, mt * BM + g * 128 + (u & 1) * 64, bar);
    };
    auto load_slab = [&](int c, uint32_t extra = 0) {
        mbar_expect_tx(ringfull + 8 * (c & 3), SLAB + extra);
        tma_load_3d(rbase + (c & 3) * SLAB, &tmq8, 0, c * BK + mt * 8, nt * 7, ringfull + 8 * (c & 3));
    };
    auto load_raw = [&](int p) {
        mbar_expect_tx(rawbar + 8 * p, 2 * SLAB);
        tma_load_3d(sbase + RAW0_OFF + p * 2 * SLAB, &tmq16, 0, rank * 32 + p * 16, nt * 7, rawbar + 8 * p);
    };
    if (warp == 7) {
        if (elect()) {
            mbar_init(rawbar, 1);
            load_raw(0);
        }
        __syncwarp();
        if (elect()) {
            mbar_init(rawbar + 8, 1);
            load_raw(1);
            mbar_init(bars + 64, 4); mbar_init(bars + 72, 4); mbar_init(bars + 104, 4); mbar_init(bars + 112, 4); mbar_init(ringfull + 16, 1);
            mbar_init_fence();
        }
        __syncwarp();
    }
    uint4 c0, c1;
    asm volatile("ld.global.nc.v4.u32 {%0, %1, %2, %3}, [%8];\nld.global.nc.v4.u32 {%4, %5, %6, %7}, [%8 + 16];"
                 : "=r"(c0.x), "=r"(c0.y), "=r"(c0.z), "=r"(c0.w), "=r"(c1.x), "=r"(c1.y), "=r"(c1.z), "=r"(c1.w) : "l"(cb));
    uint2 sc1;
    asm volatile("ld.global.nc.v2.u32 {%0, %1}, [%2];" : "=r"(sc1.x), "=r"(sc1.y) : "l"(absmax + N_ + nt * BN + (warp < 7 ? warp * 32 : 0) + (lane & 7) * 4));
    uint4 sc0;
    asm volatile("ld.global.nc.v4.u32 {%0, %1, %2, %3}, [%4];" : "=r"(sc0.x), "=r"(sc0.y), "=r"(sc0.z), "=r"(sc0.w) : "l"(absmax + nt * BN + (warp < 7 ? warp * 32 : 0) + (lane >> 3) * 8));
    if (warp < 7) {
        delay(200);
        const uint8_t* p0 = share + (lane & 1) * (4 * N_ * 4);
        asm volatile("prefetch.global.L2 [%0];" ::"l"(p0));
        if (blockIdx.x < 64) asm volatile("prefetch.global.L2 [%0];" ::"l"(p0 + 32 * N_ * 4));
    }
    if (warp == 5 || warp == 6) {
        if (elect()) {
            if (warp == 6) {
#pragma unroll
                for (int s = 0; s < 5; s++) mbar_init(wfull + 8 * s, 1);
#pragma unroll
                for (int s = 0; s < 4; s++) mbar_init(wempty + 8 * s, 16);
                mbar_init(wown, 7); mbar_init(wlast, 1); mbar_init(ringfull, 1); mbar_init(ringfull + 24, 1);
                mbar_expect_tx(wfull, W_BYTES / 2);
            }
            if (warp == 5) {
#pragma unroll
                for (int s = 0; s < 10; s++) if (s % 5 >= 2) mbar_init(bars + 64 + 8 * s, 4);
#pragma unroll
                for (int s = 1; s <= NAG; s++) mbar_init(stored + 8 * s, s == 1 ? 7 : 224);
            }
            mbar_init_fence();
        }
        __syncwarp();
    }
    cluster_arrive();
    if (warp == 7) {
        if (elect()) { load_x64(0, 0); load_x64(0, 1); load_x64(1, 0); load_x64(1, 1); }
        __syncwarp();
    }
    const uint32_t rlane = (lane & 7) * 128 + ((((lane >> 3) * 2) ^ (lane & 7)) << 4);
    const uint32_t wlane = warp * 1024 + (lane & 7) * 16 + (lane >> 3) * 4;
    const uint32_t slabsrc = __shfl_sync(~0u, (warp < 7 ? warp * 1024 + rlane : 0) + sbase, lane);
    const uint32_t scsrc = __shfl_sync(~0u, sbase + (warp < 7 ? warp * 64 : 0) + (lane >> 3) * 16, lane);
    uint8_t* const gdst = wimg + (size_t)nt * KC * W_BYTES + (mt >> 1) * SLAB + (mt & 1) * 128 + wlane;
    uint8_t* const gkeep = (uint8_t*)__shfl_sync(~0u, (unsigned long long)gdst, lane);
    uint8_t* const gread = (uint8_t*)__shfl_sync(~0u, (unsigned long long)(warp < 7 ? gdst + (lane >> 3) * 252 : (uint8_t*)flags + (lane >> 3) * 16), lane);
    Lut lut = {};
    if (warp < 7) {
        lut.lo[0] = __byte_perm(c0.x, c0.y, 0x6420); lut.hi[0] = __byte_perm(c0.x, c0.y, 0x7531);
        lut.lo[1] = __byte_perm(c0.z, c0.w, 0x6420); lut.hi[1] = __byte_perm(c0.z, c0.w, 0x7531);
        lut.lo[2] = __byte_perm(c1.x, c1.y, 0x6420); lut.hi[2] = __byte_perm(c1.x, c1.y, 0x7531);
        lut.lo[3] = __byte_perm(c1.z, c1.w, 0x6420); lut.hi[3] = __byte_perm(c1.z, c1.w, 0x7531);
    }
    cluster_wait();

    auto store_slab = [&](int c, uint32_t p, const uint4& sc) {
        const uint4 w = dequant8(p, sc, lut);
        uint8_t* g = gkeep + (size_t)c * W_BYTES;
        stg32(g, w.x); stg32(g + 256, w.y); stg32(g + 512, w.z); stg32(g + 768, w.w);
        read_l2(scsrc + SC_OFF + SC_ROW * c, gread + (size_t)c * W_BYTES, (lane & 7) == 0);
        if (c <= NAG) read_arrive(stored + 8 * c);
    };
    auto take_sample = [&]() { read_l2(scsrc + BAR_OFF, gread, (lane & 7) == 0); };
    auto load_w = [&](int c) {
        read_wait<0>();
        poll_ge(flags + c, lds32(snap + 4 * c), READY);
        asm volatile("fence.acquire.gpu;" ::: "memory");
        asm volatile("fence.proxy.async.global;" ::: "memory");
        if (c >= 4 && c < 15) mbar_wait(wempty + 8 * (c & 3), ((c >> 2) - 1) & 1);
        if (elect()) {
            if (c == 1) {
                mbar_expect_tx(wfull + 8, W_BYTES / 2);
                bulk_load_mc(wbase + W_BYTES + rank * SLAB, wsrc + W_BYTES + rank * SLAB, SLAB, wfull + 8);
                mbar_expect_tx(wlast, W_BYTES / 2);
                bulk_load_mc(wbase + W_BYTES + (2 + rank) * SLAB, wsrc + W_BYTES + (2 + rank) * SLAB, SLAB, wlast);
            } else {
                mbar_expect_tx(wfull + 8 * wbuf(c), W_BYTES);
                bulk_load_mc(wbase + wbuf(c) * W_BYTES + rank * (W_BYTES / 2), wsrc + (size_t)c * W_BYTES + rank * (W_BYTES / 2), W_BYTES / 2, wfull + 8 * wbuf(c));
            }
        }
        __syncwarp();
    };

    if (warp < 7) {
        {
            const uint4 w = dequant8(pack8(s1a, s1b), make_uint4(sc1.x, sc1.y, sc1.x, sc1.y), lut);
            uint8_t* g = wimg + (size_t)(nt * KC + 1) * W_BYTES + (mt >> 1) * SLAB + (mt & 1) * 128
                       + warp * 1024 + (lane & 1) * 512 + (lane >> 3) * 16 + ((lane & 7) >> 1) * 4;
            stg32(g, w.x); stg32(g + 64, w.z); stg32(g + 256, w.y); stg32(g + 320, w.w);
            __syncwarp();
            if (elect()) mbar_arrive(stored + 8);
            __syncwarp();
        }
        const uint32_t tab = prmt(prmt(lane & 8 ? lut.lo[2] : lut.lo[0], lane & 8 ? lut.lo[3] : lut.lo[1], lane & 7),
                                  prmt(lane & 8 ? lut.hi[2] : lut.hi[0], lane & 8 ? lut.hi[3] : lut.hi[1], lane & 7), 0x40);
#pragma unroll
        for (int p = 0; p < 2; p++) {
            mbar_wait(rawbar + 8 * p, 0);
            const uint32_t a = sbase + RAW0_OFF + p * 2 * SLAB + warp * 2048;
            const uint4 v0 = lds128(a + rlane), v1 = lds128(a + (rlane ^ 16)), v2 = lds128(a + rlane + 1024), v3 = lds128(a + (rlane ^ 16) + 1024);
            const uint4 w0 = dequant8(pack8(v0, v1), sc0, lut), w1 = dequant8_shfl(v2, v3, sc0, tab);
            const uint32_t d = wbase + (2 * rank + p) * SLAB, e = d + wlane;
            sts32(e, w0.x); sts32(e + 256, w0.y); sts32(e + 512, w0.z); sts32(e + 768, w0.w);
            sts32(e + 128, w1.x); sts32(e + 384, w1.y); sts32(e + 640, w1.z); sts32(e + 896, w1.w);
            fence_async_smem();
            __syncwarp();
            if (elect()) {
                if (p == 1) mbar_arrive(wown);
                copy_to_peer(d + warp * 1024, 1024, wfull, rank ^ 1);
            }
            __syncwarp();
        }
    } else {
        mbar_wait(stored + 8, 0);
        const uint8_t* g1 = wsrc + W_BYTES + (mt >> 1) * SLAB + (mt & 1) * 128 + (lane >> 1) * 256 + (lane & 1) * 64;
        const unsigned v0 = ld_relaxed(g1), v1 = ld_relaxed(g1 + 3072);
        if (elect()) {
            load_slab(2, 14 * SC_ROW);
            tma_load_2d(sbase + SC_OFF + 2 * SC_ROW, &tms, nt * BN, 2, ringfull + 16);
        }
        __syncwarp();
        const unsigned n = after(after(7, v0, zero), v1, zero);
        __syncwarp();
        if (elect()) red_add(flags + 1, n);
        __syncwarp();
        if (elect()) load_slab(3);
        __syncwarp();
        mbar_wait(wown, 0);
        if (elect()) { load_x64(0, 2); load_x64(0, 3); load_x64(1, 2); load_x64(1, 3); }
        __syncwarp();
    }

    float acc0[112], acc1[112];
    const uint32_t descA = ((xbase & 0x3FFFF) >> 4) | (1u << 16), descB = ((wbase & 0x3FFFF) >> 4) | ((128u >> 4) << 16);
    static_for<0, UM>([&](auto U) __attribute__((always_inline)) {
        constexpr int u = U.value, kc = u >> 1;
        constexpr int c = slab_at(u);
        uint32_t da = descA, db = descB;
        asm volatile("" : "+r"(da), "+r"(db));
        uint4 q0, q1, sc;
        auto slab_loads = [&]() {
            q0 = lds128(slabsrc + R_OFF + (c & 3) * SLAB); q1 = lds128((slabsrc ^ 16) + R_OFF + (c & 3) * SLAB);
            sc = lds128(scsrc + SC_OFF + SC_ROW * (c & 15));
        };
        if (u < 4) {
            if (u == 0) mbar_wait3(xfull, 0, xfull + 8, 0, wown, 0);
            if (u == 1) mbar_wait(wfull, 0);
            if (u == 2) mbar_wait3(xfull + 16, 0, xfull + 24, 0, wfull + 8, 0);
            if (u == 3) { mbar_wait2(wlast, 0, ringfull, 0); slab_loads(); }
            if (u == 0 && warp == 7) take_sample();
            const int h = u < 2 ? rank ^ u : u & 1;
            da += kc * 1024 + h * 4; db += kc * (W_BYTES >> 4) + h * (2 * SLAB >> 4);
            wgmma_fence();
            wgmma_ss<u != 0>(acc0, da, db); wgmma_ss<u != 0>(acc1, da + 512, db);
            wgmma_ss<1>(acc0, da + 2, db + (SLAB >> 4)); wgmma_ss<1>(acc1, da + 514, db + (SLAB >> 4));
        } else {
            if (u & 1) mbar_wait(xfull + 8 * (u % 5), (u / 5) & 1);
            else mbar_wait2(xfull + 8 * (u % 5), (u / 5) & 1, wfull + 8 * (kc & 3), (kc >> 2) & 1);
            if (c >= 0) slab_loads();
            da += (u % 5) * 512; db += (kc & 3) * (W_BYTES >> 4);
            wgmma_fence();
#pragma unroll
            for (int ks = 0; ks < 4; ks++) {
                if (u & 1) wgmma_ss<1>(acc1, da + ks * 2, db + ks * (SLAB >> 4));
                else wgmma_ss<1>(acc0, da + ks * 2, db + ks * (SLAB >> 4));
            }
        }
        wgmma_commit();
        if (u >= 2) wgmma_wait<1>();
        if (warp < 7) {
            constexpr int cp = slab_at(u - 2) > NAG ? slab_at(u - 2) : -1;
            if constexpr (u < 2) { mbar_wait(ringfull + 8 * c, 0); slab_loads(); }
            uint32_t p = 0;
            if (c >= 0) p = pack8(q0, q1);
            if (cp >= 0) { if (slab_at(u - 1) >= 0) read_wait<1>(); else read_wait<0>(); }
            if (u >= 2) {
                if (elect()) {
                    if (u <= 17) load_x(u + 3, slab_at(u + 3));
                    if (u >= 17) load_x(u + 4);
                    if (!(u & 1)) mbar_arrive_both(wempty + 8 * ((kc - 1) & 3));
                    if (cp >= 0) red_add(flags + cp, 1);
                }
                __syncwarp();
            }
            if (c >= 0) store_slab(c, p, sc);
        } else {
            constexpr int cw = wload_at(u), cc = slab_at(u - 1) <= NAG ? slab_at(u - 1) : -1;
            if (cw >= 0 && cw <= 6) load_w(cw);
            if (u != 1) {
                if (elect()) {
                    if (u == 0) load_slab(4);
                    if (u >= 2 && u <= 17) load_x(u + 3);
                    if (u >= 17) load_x(u + 4);
                    if (u >= 2 && !(u & 1)) mbar_arrive_both(wempty + 8 * ((kc - 1) & 3));
                }
                __syncwarp();
            }
            if constexpr (cc >= 0) {
                mbar_wait(stored + 8 * cc, 0);
                if (elect()) red_add(flags + cc, 7);
                __syncwarp();
            }
            if (u == 1) {
                if (elect()) { load_x64(0, 4); load_x64(1, 4); }
                __syncwarp();
                delay(300);
            }
            if (cw > 6) load_w(cw);
            if (wload_at(u + 1) >= 0) take_sample();
        }
    });

    uint32_t tA = descA, tB = descB;
    asm volatile("" : "+r"(tA), "+r"(tB));
    if (wg == 1) {
        wgmma_wait<0>();
        if (elect()) { load_x(UM + 4); mbar_arrive_both(wempty + 16); }
        __syncwarp();
        if (warp == 7) load_w(14);
        if (warp == 7 && lane == 0) {
            if (atomicAdd(flags + 16, 1) == MT - 1) {
#pragma unroll
                for (int c = 0; c <= 16; c++) flags[c] = 0;
            }
        }
        __syncwarp();
        bar_sync<256>(1);
    }
#pragma unroll
    for (int j = 0; j < 5; j++) {
        const int c = tail_chunk(j), v = UM + j;
        mbar_wait2(xfull + 8 * (v % 5), (v / 5) & 1, wfull + 8 * wbuf(c), c == 15 ? 0 : (c >> 2) & 1);
        wgmma_fence();
#pragma unroll
        for (int ks = 0; ks < 4; ks++) wgmma_ss<1>(acc0, tA + (v % 5) * 512 + ks * 2, tB + wbuf(c) * (W_BYTES >> 4) + ks * (SLAB >> 4));
        wgmma_commit();
        if (j == 4) bar_arrive<256>(1 + wg);
        if (j == 0) {
            if (wg == 0) {
                wgmma_wait<1>();
                if (elect()) { load_x(UM + 4); mbar_arrive_both(wempty + 16); }
                __syncwarp();
            }
        } else if (j >= 2) {
            wgmma_wait<2>();
            if (elect()) load_x(v + 3);
            __syncwarp();
        }
    }
    wgmma_wait<1>();
    if (elect()) load_x(UM + 8);
    __syncwarp();
    wgmma_wait<0>();
    if (elect()) load_x(UM + 9);
    __syncwarp();
    uint8_t* optr = out + (size_t)(xrow + (lane >> 2)) * (N_ * 2) + nt * (BN * 2) + (lane & 3) * 16;
    float pa[64], pb[32], pc[16];
#pragma unroll
    for (int i = 0; i < 64; i++) asm volatile("mov.b32 %0, %1;" : "=f"(pa[i]) : "f"(acc1[i]));
#pragma unroll
    for (int i = 0; i < 32; i++) asm volatile("mov.b32 %0, %1;" : "=f"(pb[i]) : "f"(acc1[64 + i]));
#pragma unroll
    for (int i = 0; i < 16; i++) asm volatile("mov.b32 %0, %1;" : "=f"(pc[i]) : "f"(acc1[96 + i]));
    uint4 af[20];
    uint32_t pk[56];
    auto store_pk = [&](int h0, int h1) {
#pragma unroll
        for (int h = h0; h < h1; h++) {
            const int i = 8 * (h >> 1) + (h & 1);
            stg128(optr + (h >> 1) * 64 + (h & 1) * (8 * N_ * 2), pk[i], pk[i + 2], pk[i + 4], pk[i + 6]);
        }
    };
    const uint32_t alane = xbase + wj * 2048 + (lane & 15) * 128 + (((lane >> 4) ^ (lane & 7)) << 4);
    static_for<0, 4>([&](auto J) __attribute__((always_inline)) {
        constexpr int j = J.value, v = UM + 5 + j;
        mbar_wait(xfull + 8 * (v % 5), (v / 5) & 1);
#pragma unroll
        for (int ks = 0; ks < 4; ks++) af[4 * j + ks] = ldmatrix_x4((alane ^ (ks * 32)) + (v % 5) * 8192);
#pragma unroll
        for (int i = 16 * j; i < (j < 3 ? 16 * j + 16 : 56); i++) pk[i] = pack_bf16(acc0[2 * i], acc0[2 * i + 1]);
        store_pk(2 * j, 2 * j + 2);
    });
    store_pk(8, 10);
    if (wg == 0) store_pk(10, 14);
    auto piece = [&](auto& d, auto CB) {
        constexpr int cb = CB.value;
        wgmma_fence();
#pragma unroll
        for (int j = 0; j < 5; j++) {
            if (cb == 0 && j == 4) { mbar_wait(xfull + 8 * ((UM + 9) % 5), ((UM + 9) / 5) & 1); wgmma_fence(); }
#pragma unroll
            for (int ks = 0; ks < 4; ks++) {
                const uint32_t db = tB + wbuf(tail_chunk(j)) * (W_BYTES >> 4) + ks * (SLAB >> 4) + cb * 64;
                if (j < 4 || cb > 0) wgmma_rs(d, af[4 * j + ks], db);
                else if constexpr (cb == 0) wgmma_ss<1>(d, tA + ((UM + 9) % 5) * 512 + ks * 2, db);
            }
        }
        wgmma_commit();
    };
    bar_sync<256>(2 + wg);
    piece(pa, IC<0>{});
    bar_arrive<256>(3 + wg);
    if (wg == 1) store_pk(10, 14);
    wgmma_wait<0>();
#pragma unroll
    for (int ks = 0; ks < 4; ks++) af[16 + ks] = ldmatrix_x4((alane ^ (ks * 32)) + ((UM + 9) % 5) * 8192);
    optr += 64 * N_ * 2;
    store_cols(pa, optr);
    bar_sync<256>(4 + wg);
    piece(pb, IC<4>{});
    bar_arrive<256>(5 + wg);
    wgmma_wait<0>();
    store_cols(pb, optr + 4 * 64);
    bar_sync<256>(6 + wg);
    piece(pc, IC<6>{});
    if (wg == 0) bar_arrive<256>(7);
    cluster_arrive();
    wgmma_wait<0>();
    store_cols(pc, optr + 6 * 64);
    cluster_wait();
}

typedef CUresult (*EncodeFn)(CUtensorMap*, CUtensorMapDataType, cuuint32_t, void*, const cuuint64_t*, const cuuint64_t*,
                             const cuuint32_t*, const cuuint32_t*, CUtensorMapInterleave, CUtensorMapSwizzle,
                             CUtensorMapL2promotion, CUtensorMapFloatOOBfill);

extern "C" void kernel_launch(void* const* d_in, const int* in_sizes, int n_in, void* d_out, int out_size) {
    static EncodeFn encode = nullptr;
    static void *wimg = nullptr, *gflags = nullptr;
    if (!encode) {
        cudaGetSymbolAddress(&wimg, g_wimg);
        cudaGetSymbolAddress(&gflags, g_flag);
        void* fn = nullptr;
        cudaDriverEntryPointQueryResult qr;
        cudaGetDriverEntryPoint("cuTensorMapEncodeTiled", &fn, cudaEnableDefault, &qr);
        encode = (EncodeFn)fn;
        cudaFuncSetAttribute(nf4_gemm_kernel, cudaFuncAttributeMaxDynamicSharedMemorySize, SMEM_BYTES);
    }
    void *x = d_in[0], *qw = d_in[1], *cb = d_in[2], *absmax = d_in[3];
    auto map = [&](CUtensorMapDataType t, int rank, void* p, const cuuint64_t* dims, const cuuint64_t* strides, const cuuint32_t* box, bool swizzle) {
        CUtensorMap m;
        const cuuint32_t es[3] = {1, 1, 1};
        encode(&m, t, rank, p, dims, strides, box, es, CU_TENSOR_MAP_INTERLEAVE_NONE,
               swizzle ? CU_TENSOR_MAP_SWIZZLE_128B : CU_TENSOR_MAP_SWIZZLE_NONE,
               swizzle ? CU_TENSOR_MAP_L2_PROMOTION_L2_128B : CU_TENSOR_MAP_L2_PROMOTION_NONE, CU_TENSOR_MAP_FLOAT_OOB_FILL_NONE);
        return m;
    };
    const cuuint64_t xd[2] = {K_, M_}, xs[1] = {K_ * 2};
    const cuuint64_t q3d[3] = {32, K_, N_ / 32}, q3s[2] = {N_ * 4, 128};
    const cuuint64_t q2d[2] = {N_, K_}, q2s[1] = {N_ * 4};
    const cuuint64_t sd[2] = {N_, KC}, ss[1] = {N_ * 2};
    const cuuint32_t bx[2] = {BK, 16}, bx64[2] = {BK, 64}, bq16[3] = {32, 16, 7}, bq8[3] = {32, 8, 7}, bq1[2] = {32, 8}, bs[2] = {BN, KC - 2};
    nf4_gemm_kernel<<<128, 256, SMEM_BYTES>>>(
        (const uint8_t*)qw, (const __nv_bfloat16*)cb, (const __nv_bfloat16*)absmax, (uint8_t*)wimg, (unsigned*)gflags, (uint8_t*)d_out, 0u,
        map(CU_TENSOR_MAP_DATA_TYPE_BFLOAT16, 2, x, xd, xs, bx, true), map(CU_TENSOR_MAP_DATA_TYPE_BFLOAT16, 2, x, xd, xs, bx64, true),
        map(CU_TENSOR_MAP_DATA_TYPE_INT32, 3, qw, q3d, q3s, bq16, true), map(CU_TENSOR_MAP_DATA_TYPE_INT32, 3, qw, q3d, q3s, bq8, true),
        map(CU_TENSOR_MAP_DATA_TYPE_INT32, 2, qw, q2d, q2s, bq1, true), map(CU_TENSOR_MAP_DATA_TYPE_BFLOAT16, 2, absmax, sd, ss, bs, false));
}
```

```cpp
#include <cuda_runtime.h>
#include <cuda_bf16.h>
#include <cuda.h>
#include <stdint.h>

constexpr int M_ = 2048, K_ = 1024, N_ = 3584;
constexpr int BM = 256, BN = 224, BK = 64;
constexpr int KC = K_ / BK;

__device__ __forceinline__ uint32_t smem_u32(const void* p) { return (uint32_t)__cvta_generic_to_shared(p); }
__device__ __forceinline__ bool elect() {
    uint32_t ok;
    asm volatile("{\n.reg .pred p;\nelect.sync _|p, 0xffffffff;\nselp.u32 %0, 1, 0, p;\n}\n" : "=r"(ok));
    return ok != 0;
}
template <int I> struct IC { static constexpr int value = I; };
template <int I, int N, class F> __device__ __forceinline__ void static_for(F&& f) {
    if constexpr (I < N) { f(IC<I>{}); static_for<I + 1, N>(f); }
}

__device__ __forceinline__ void mbar_init(uint32_t bar, uint32_t cnt) { asm volatile("mbarrier.init.shared::cta.b64 [%0], %1;" ::"r"(bar), "r"(cnt) : "memory"); }
__device__ __forceinline__ void mbar_init_fence() { asm volatile("fence.mbarrier_init.release.cluster;" ::: "memory"); }
__device__ __forceinline__ void mbar_expect_tx(uint32_t bar, uint32_t bytes) { asm volatile("mbarrier.arrive.expect_tx.shared::cta.b64 _, [%0], %1;" ::"r"(bar), "r"(bytes) : "memory"); }
__device__ __forceinline__ void mbar_arrive(uint32_t bar) { asm volatile("mbarrier.arrive.shared::cta.b64 _, [%0];" ::"r"(bar) : "memory"); }
__device__ __forceinline__ void mbar_arrive_n(uint32_t bar, uint32_t n) { asm volatile("mbarrier.arrive.shared::cta.b64 _, [%0], %1;" ::"r"(bar), "r"(n) : "memory"); }
__device__ __forceinline__ void mbar_arrive_both(uint32_t bar) {
    asm volatile("{\n.reg .b32 ra;\nmapa.shared::cluster.u32 ra, %0, 0;\nmbarrier.arrive.shared::cluster.b64 _, [ra];\n"
                 "mapa.shared::cluster.u32 ra, %0, 1;\nmbarrier.arrive.shared::cluster.b64 _, [ra];\n}\n" ::"r"(bar) : "memory");
}
#define MBAR_TRY(p, b, q) "mbarrier.try_wait.parity.shared::cta.b64 " p ", [" b "], " q ";\n"
#define MBAR_WAIT(TRY) \
    "{\n.reg .pred p0, p1, p2;\n.reg .b32 n;\n" TRY "@p0 bra LAB_DONE;\nmov.b32 n, 0;\nLAB_WAIT:\n" TRY \
    "@p0 bra LAB_DONE;\nadd.u32 n, n, 1;\nsetp.lt.u32 p0, n, 0x40000;\n@p0 bra LAB_WAIT;\ntrap;\nLAB_DONE:\n}\n"
__device__ __forceinline__ void mbar_wait(uint32_t b0, uint32_t q0) {
    asm volatile(MBAR_WAIT(MBAR_TRY("p0", "%0", "%1")) ::"r"(b0), "r"(q0) : "memory");
}
__device__ __forceinline__ void mbar_wait2(uint32_t b0, uint32_t q0, uint32_t b1, uint32_t q1) {
    asm volatile(MBAR_WAIT(MBAR_TRY("p0", "%0", "%1") MBAR_TRY("p1", "%2", "%3") "and.pred p0, p0, p1;\n")
                 ::"r"(b0), "r"(q0), "r"(b1), "r"(q1) : "memory");
}
__device__ __forceinline__ void mbar_wait3(uint32_t b0, uint32_t q0, uint32_t b1, uint32_t q1, uint32_t b2, uint32_t q2) {
    asm volatile(MBAR_WAIT(MBAR_TRY("p0", "%0", "%1") MBAR_TRY("p1", "%2", "%3") MBAR_TRY("p2", "%4", "%5") "and.pred p0, p0, p1;\nand.pred p0, p0, p2;\n")
                 ::"r"(b0), "r"(q0), "r"(b1), "r"(q1), "r"(b2), "r"(q2) : "memory");
}
__device__ __forceinline__ void cluster_arrive() { asm volatile("barrier.cluster.arrive.relaxed.aligned;" ::: "memory"); }
__device__ __forceinline__ void cluster_wait() { asm volatile("barrier.cluster.wait.acquire.aligned;" ::: "memory"); }
template <int NTHR> __device__ __forceinline__ void bar_arrive(int id) { asm volatile("bar.arrive %0, %1;" ::"r"(id), "n"(NTHR) : "memory"); }
template <int NTHR> __device__ __forceinline__ void bar_sync(int id) { asm volatile("bar.sync %0, %1;" ::"r"(id), "n"(NTHR) : "memory"); }
__device__ __forceinline__ void delay(unsigned clks) {
    asm volatile(
        "{\n.reg .pred p;\n.reg .b32 t0, t;\n"
        "mov.u32 t0, %%clock;\n"
        "LAB_DELAY:\n"
        "mov.u32 t, %%clock;\n"
        "sub.u32 t, t, t0;\n"
        "setp.lt.u32 p, t, %0;\n"
        "vote.sync.any.pred p, p, 0xffffffff;\n"
        "@p bra.uni LAB_DELAY;\n}\n" ::"r"(clks) : "memory");
}

__device__ __forceinline__ void tma_load_2d(uint32_t dst, const CUtensorMap* tm, int c0, int c1, uint32_t bar) {
    asm volatile("cp.async.bulk.tensor.2d.shared::cluster.global.mbarrier::complete_tx::bytes [%0], [%1, {%2, %3}], [%4];"
                 ::"r"(dst), "l"(tm), "r"(c0), "r"(c1), "r"(bar) : "memory");
}
__device__ __forceinline__ void tma_load_3d(uint32_t dst, const CUtensorMap* tm, int c0, int c1, int c2, uint32_t bar) {
    asm volatile("cp.async.bulk.tensor.3d.shared::cluster.global.mbarrier::complete_tx::bytes [%0], [%1, {%2, %3, %4}], [%5];"
                 ::"r"(dst), "l"(tm), "r"(c0), "r"(c1), "r"(c2), "r"(bar) : "memory");
}
__device__ __forceinline__ void bulk_load_mc(uint32_t dst, const void* src, uint32_t bytes, uint32_t bar) {
    asm volatile("cp.async.bulk.shared::cluster.global.mbarrier::complete_tx::bytes.multicast::cluster [%0], [%1], %2, [%3], %4;"
                 ::"r"(dst), "l"(src), "r"(bytes), "r"(bar), "h"((uint16_t)3) : "memory");
}
__device__ __forceinline__ uint32_t mapa(uint32_t addr, uint32_t cta) {
    uint32_t r; asm("mapa.shared::cluster.u32 %0, %1, %2;" : "=r"(r) : "r"(addr), "r"(cta)); return r;
}
__device__ __forceinline__ void copy_to_peer(uint32_t addr, uint32_t bytes, uint32_t bar, uint32_t peer) {
    asm volatile("cp.async.bulk.shared::cluster.shared::cta.mbarrier::complete_tx::bytes [%0], [%1], %2, [%3];"
                 ::"r"(mapa(addr, peer)), "r"(addr), "r"(bytes), "r"(mapa(bar, peer)) : "memory");
}
__device__ __forceinline__ void fence_async_smem() { asm volatile("fence.proxy.async.shared::cta;" ::: "memory"); }

__device__ __forceinline__ uint4 lds128(uint32_t a) {
    uint4 v; asm volatile("ld.shared.v4.b32 {%0, %1, %2, %3}, [%4];" : "=r"(v.x), "=r"(v.y), "=r"(v.z), "=r"(v.w) : "r"(a) : "memory"); return v;
}
__device__ __forceinline__ uint32_t lds32(uint32_t a) {
    uint32_t v; asm volatile("ld.shared.b32 %0, [%1];" : "=r"(v) : "r"(a) : "memory"); return v;
}
__device__ __forceinline__ uint4 ldmatrix_x4(uint32_t a) {
    uint4 v;
    asm volatile("ldmatrix.sync.aligned.m8n8.x4.shared.b16 {%0, %1, %2, %3}, [%4];" : "=r"(v.x), "=r"(v.y), "=r"(v.z), "=r"(v.w) : "r"(a) : "memory");
    return v;
}
__device__ __forceinline__ void sts32(uint32_t a, uint32_t v) { asm volatile("st.shared.b32 [%0], %1;" ::"r"(a), "r"(v) : "memory"); }
__device__ __forceinline__ void stg32(void* p, uint32_t v) { asm volatile("st.global.b32 [%0], %1;" ::"l"(p), "r"(v) : "memory"); }
__device__ __forceinline__ void stg128(void* p, uint32_t a, uint32_t b, uint32_t c, uint32_t d) {
    asm volatile("st.global.v4.b32 [%0], {%1, %2, %3, %4};" ::"l"(p), "r"(a), "r"(b), "r"(c), "r"(d) : "memory");
}

__device__ __forceinline__ unsigned ld_relaxed(const void* p) {
    unsigned v; asm volatile("ld.relaxed.gpu.global.u32 %0, [%1];" : "=r"(v) : "l"(p) : "memory"); return v;
}
__device__ __forceinline__ void read_l2(uint32_t dst, const void* src, uint32_t on) {
    asm volatile("{\n.reg .pred p;\nsetp.ne.u32 p, %2, 0;\n@p cp.async.cg.shared.global [%0], [%1], 16;\n}\ncp.async.commit_group;" ::"r"(dst), "l"(src), "r"(on) : "memory");
}
template <int N> __device__ __forceinline__ void read_wait() { asm volatile("cp.async.wait_group %0;" ::"n"(N) : "memory"); __syncwarp(); }
__device__ __forceinline__ void read_arrive(uint32_t bar) { asm volatile("cp.async.mbarrier.arrive.noinc.shared::cta.b64 [%0];" ::"r"(bar) : "memory"); }
__device__ __forceinline__ unsigned after(unsigned n, unsigned p, unsigned z) {
    unsigned r; asm volatile("lop3.b32 %0, %1, %2, %3, 0xea;" : "=r"(r) : "r"(p), "r"(z), "r"(n)); return r;
}
__device__ __forceinline__ void red_add(unsigned* f, unsigned n) { asm volatile("red.relaxed.gpu.global.add.u32 [%0], %1;" ::"l"(f), "r"(n) : "memory"); }
__device__ __forceinline__ void poll_ge(const unsigned* f, unsigned v, unsigned ready) {
    asm volatile(
        "{\n.reg .pred p;\n.reg .b32 v, n;\n"
        "setp.lt.u32 p, %1, %2;\n"
        "vote.sync.any.pred p, p, 0xffffffff;\n"
        "@!p bra.uni LAB_DONE;\n"
        "mov.b32 n, 0;\n"
        "LAB_POLL:\n"
        "ld.relaxed.gpu.global.u32 v, [%0];\n"
        "setp.lt.u32 p, v, %2;\n"
        "vote.sync.any.pred p, p, 0xffffffff;\n"
        "@!p bra.uni LAB_DONE;\n"
        "add.u32 n, n, 1;\n"
        "setp.lt.u32 p, n, 0x400000;\n"
        "@p bra.uni LAB_POLL;\n"
        "LAB_DONE:\n}\n" ::"l"(f), "r"(v), "r"(ready) : "memory");
}

__device__ __forceinline__ uint32_t pack_bf16(float lo, float hi) {
    uint32_t r; asm("cvt.rn.bf16x2.f32 %0, %1, %2;" : "=r"(r) : "f"(hi), "f"(lo)); return r;
}
__device__ __forceinline__ uint32_t mul_bf16x2(uint32_t a, uint32_t b) { uint32_t r; asm("mul.rn.bf16x2 %0, %1, %2;" : "=r"(r) : "r"(a), "r"(b)); return r; }
__device__ __forceinline__ uint32_t prmt(uint32_t a, uint32_t b, uint32_t s) { uint32_t r; asm("prmt.b32 %0, %1, %2, %3;" : "=r"(r) : "r"(a), "r"(b), "r"(s)); return r; }
__device__ __forceinline__ uint32_t madi(uint32_t hi, uint32_t m, uint32_t lo) { uint32_t r; asm("mad.lo.u32 %0, %1, %2, %3;" : "=r"(r) : "r"(hi), "r"(m), "r"(lo)); return r; }
__device__ __forceinline__ uint32_t pack8(const uint4& a, const uint4& b) {
    return madi(madi(madi(b.w, 65536, a.w), 16, madi(b.z, 65536, a.z)), 256, madi(madi(b.y, 65536, a.y), 16, madi(b.x, 65536, a.x)));
}
struct Lut { uint32_t lo[4], hi[4]; };
__device__ __forceinline__ void lookup4(uint32_t s7, uint32_t sel, const Lut& t, uint32_t& w01, uint32_t& w23) {
    const uint32_t lo = prmt(prmt(t.lo[0], t.lo[1], s7), prmt(t.lo[2], t.lo[3], s7), sel);
    const uint32_t hi = prmt(prmt(t.hi[0], t.hi[1], s7), prmt(t.hi[2], t.hi[3], s7), sel);
    w01 = prmt(lo, hi, 0x5140);
    w23 = prmt(lo, hi, 0x7362);
}
__device__ __forceinline__ uint4 dequant8(uint32_t p, const uint4& sc, const Lut& t) {
    const uint32_t m8 = p & 0x88888888u, s7 = p & 0x77777777u;
    uint4 r;
    lookup4(s7, (m8 >> 1) + 0x3210u, t, r.x, r.y);
    lookup4(s7 >> 16, (m8 >> 17) + 0x3210u, t, r.z, r.w);
    r.x = mul_bf16x2(r.x, sc.x); r.y = mul_bf16x2(r.y, sc.y); r.z = mul_bf16x2(r.z, sc.z); r.w = mul_bf16x2(r.w, sc.w);
    return r;
}
__device__ __forceinline__ uint4 dequant8_shfl(const uint4& q0, const uint4& q1, const uint4& sc, uint32_t tab) {
    uint4 r;
    r.x = mul_bf16x2(__byte_perm(__shfl_sync(~0u, tab, q0.x), __shfl_sync(~0u, tab, q0.y), 0x5410), sc.x);
    r.y = mul_bf16x2(__byte_perm(__shfl_sync(~0u, tab, q0.z), __shfl_sync(~0u, tab, q0.w), 0x5410), sc.y);
    r.z = mul_bf16x2(__byte_perm(__shfl_sync(~0u, tab, q1.x), __shfl_sync(~0u, tab, q1.y), 0x5410), sc.z);
    r.w = mul_bf16x2(__byte_perm(__shfl_sync(~0u, tab, q1.z), __shfl_sync(~0u, tab, q1.w), 0x5410), sc.w);
    return r;
}

__device__ __forceinline__ void wgmma_fence() { asm volatile("wgmma.fence.sync.aligned;" ::: "memory"); }
__device__ __forceinline__ void wgmma_commit() { asm volatile("wgmma.commit_group.sync.aligned;" ::: "memory"); }
template <int N> __device__ __forceinline__ void wgmma_wait() { asm volatile("wgmma.wait_group.sync.aligned %0;" ::"n"(N) : "memory"); }
template <int SCALE_D>
__device__ __forceinline__ void wgmma_ss(float (&d)[112], uint32_t descA, uint32_t descB) {
    asm volatile(
        "{\n.reg .pred p;\n.reg .b64 da, db;\nsetp.ne.b32 p, %114, 0;\n"
        "mov.b64 da, {%112, 0x40000040};\nmov.b64 db, {%113, 0x10};\n"
        "wgmma.mma_async.sync.aligned.m64n224k16.f32.bf16.bf16 "
        "{%0, %1, %2, %3, %4, %5, %6, %7, %8, %9, %10, %11, %12, %13, %14, %15, "
        "%16, %17, %18, %19, %20, %21, %22, %23, %24, %25, %26, %27, %28, %29, %30, %31, "
        "%32, %33, %34, %35, %36, %37, %38, %39, %40, %41, %42, %43, %44, %45, %46, %47, "
        "%48, %49, %50, %51, %52, %53, %54, %55, %56, %57, %58, %59, %60, %61, %62, %63, "
        "%64, %65, %66, %67, %68, %69, %70, %71, %72, %73, %74, %75, %76, %77, %78, %79, "
        "%80, %81, %82, %83, %84, %85, %86, %87, %88, %89, %90, %91, %92, %93, %94, %95, "
        "%96, %97, %98, %99, %100, %101, %102, %103, %104, %105, %106, %107, %108, %109, %110, %111}, "
        "da, db, p, 1, 1, 0, 1;\n}\n"
        : "+f"(d[0]), "+f"(d[1]), "+f"(d[2]), "+f"(d[3]), "+f"(d[4]), "+f"(d[5]), "+f"(d[6]), "+f"(d[7]),
          "+f"(d[8]), "+f"(d[9]), "+f"(d[10]), "+f"(d[11]), "+f"(d[12]), "+f"(d[13]), "+f"(d[14]), "+f"(d[15]),
          "+f"(d[16]), "+f"(d[17]), "+f"(d[18]), "+f"(d[19]), "+f"(d[20]), "+f"(d[21]), "+f"(d[22]), "+f"(d[23]),
          "+f"(d[24]), "+f"(d[25]), "+f"(d[26]), "+f"(d[27]), "+f"(d[28]), "+f"(d[29]), "+f"(d[30]), "+f"(d[31]),
          "+f"(d[32]), "+f"(d[33]), "+f"(d[34]), "+f"(d[35]), "+f"(d[36]), "+f"(d[37]), "+f"(d[38]), "+f"(d[39]),
          "+f"(d[40]), "+f"(d[41]), "+f"(d[42]), "+f"(d[43]), "+f"(d[44]), "+f"(d[45]), "+f"(d[46]), "+f"(d[47]),
          "+f"(d[48]), "+f"(d[49]), "+f"(d[50]), "+f"(d[51]), "+f"(d[52]), "+f"(d[53]), "+f"(d[54]), "+f"(d[55]),
          "+f"(d[56]), "+f"(d[57]), "+f"(d[58]), "+f"(d[59]), "+f"(d[60]), "+f"(d[61]), "+f"(d[62]), "+f"(d[63]),
          "+f"(d[64]), "+f"(d[65]), "+f"(d[66]), "+f"(d[67]), "+f"(d[68]), "+f"(d[69]), "+f"(d[70]), "+f"(d[71]),
          "+f"(d[72]), "+f"(d[73]), "+f"(d[74]), "+f"(d[75]), "+f"(d[76]), "+f"(d[77]), "+f"(d[78]), "+f"(d[79]),
          "+f"(d[80]), "+f"(d[81]), "+f"(d[82]), "+f"(d[83]), "+f"(d[84]), "+f"(d[85]), "+f"(d[86]), "+f"(d[87]),
          "+f"(d[88]), "+f"(d[89]), "+f"(d[90]), "+f"(d[91]), "+f"(d[92]), "+f"(d[93]), "+f"(d[94]), "+f"(d[95]),
          "+f"(d[96]), "+f"(d[97]), "+f"(d[98]), "+f"(d[99]), "+f"(d[100]), "+f"(d[101]), "+f"(d[102]), "+f"(d[103]),
          "+f"(d[104]), "+f"(d[105]), "+f"(d[106]), "+f"(d[107]), "+f"(d[108]), "+f"(d[109]), "+f"(d[110]), "+f"(d[111])
        : "r"(descA), "r"(descB), "n"(SCALE_D));
}

template <int SCALE_D>
__device__ __forceinline__ void wgmma_ss(float (&d)[64], uint32_t descA, uint32_t descB) {
    asm volatile(
        "{\n.reg .pred p;\n.reg .b64 da, db;\nsetp.ne.b32 p, %66, 0;\n"
        "mov.b64 da, {%64, 0x40000040};\nmov.b64 db, {%65, 0x10};\n"
        "wgmma.mma_async.sync.aligned.m64n128k16.f32.bf16.bf16 "
        "{%0, %1, %2, %3, %4, %5, %6, %7, %8, %9, %10, %11, %12, %13, %14, %15, "
        "%16, %17, %18, %19, %20, %21, %22, %23, %24, %25, %26, %27, %28, %29, %30, %31, "
        "%32, %33, %34, %35, %36, %37, %38, %39, %40, %41, %42, %43, %44, %45, %46, %47, "
        "%48, %49, %50, %51, %52, %53, %54, %55, %56, %57, %58, %59, %60, %61, %62, %63}, "
        "da, db, p, 1, 1, 0, 1;\n}\n"
        : "+f"(d[0]), "+f"(d[1]), "+f"(d[2]), "+f"(d[3]), "+f"(d[4]), "+f"(d[5]), "+f"(d[6]), "+f"(d[7]),
          "+f"(d[8]), "+f"(d[9]), "+f"(d[10]), "+f"(d[11]), "+f"(d[12]), "+f"(d[13]), "+f"(d[14]), "+f"(d[15]),
          "+f"(d[16]), "+f"(d[17]), "+f"(d[18]), "+f"(d[19]), "+f"(d[20]), "+f"(d[21]), "+f"(d[22]), "+f"(d[23]),
          "+f"(d[24]), "+f"(d[25]), "+f"(d[26]), "+f"(d[27]), "+f"(d[28]), "+f"(d[29]), "+f"(d[30]), "+f"(d[31]),
          "+f"(d[32]), "+f"(d[33]), "+f"(d[34]), "+f"(d[35]), "+f"(d[36]), "+f"(d[37]), "+f"(d[38]), "+f"(d[39]),
          "+f"(d[40]), "+f"(d[41]), "+f"(d[42]), "+f"(d[43]), "+f"(d[44]), "+f"(d[45]), "+f"(d[46]), "+f"(d[47]),
          "+f"(d[48]), "+f"(d[49]), "+f"(d[50]), "+f"(d[51]), "+f"(d[52]), "+f"(d[53]), "+f"(d[54]), "+f"(d[55]),
          "+f"(d[56]), "+f"(d[57]), "+f"(d[58]), "+f"(d[59]), "+f"(d[60]), "+f"(d[61]), "+f"(d[62]), "+f"(d[63])
        : "r"(descA), "r"(descB), "n"(SCALE_D));
}

__device__ __forceinline__ void wgmma_rs(float (&d)[64], const uint4& a, uint32_t descB) {
    asm volatile(
        "{\n.reg .pred p;\n.reg .b64 db;\nsetp.eq.b32 p, 0, 0;\n"
        "mov.b64 db, {%68, 0x10};\n"
        "wgmma.mma_async.sync.aligned.m64n128k16.f32.bf16.bf16 "
        "{%0, %1, %2, %3, %4, %5, %6, %7, %8, %9, %10, %11, %12, %13, %14, %15, "
        "%16, %17, %18, %19, %20, %21, %22, %23, %24, %25, %26, %27, %28, %29, %30, %31, "
        "%32, %33, %34, %35, %36, %37, %38, %39, %40, %41, %42, %43, %44, %45, %46, %47, "
        "%48, %49, %50, %51, %52, %53, %54, %55, %56, %57, %58, %59, %60, %61, %62, %63}, "
        "{%64, %65, %66, %67}, db, p, 1, 1, 1;\n}\n"
        : "+f"(d[0]), "+f"(d[1]), "+f"(d[2]), "+f"(d[3]), "+f"(d[4]), "+f"(d[5]), "+f"(d[6]), "+f"(d[7]),
          "+f"(d[8]), "+f"(d[9]), "+f"(d[10]), "+f"(d[11]), "+f"(d[12]), "+f"(d[13]), "+f"(d[14]), "+f"(d[15]),
          "+f"(d[16]), "+f"(d[17]), "+f"(d[18]), "+f"(d[19]), "+f"(d[20]), "+f"(d[21]), "+f"(d[22]), "+f"(d[23]),
          "+f"(d[24]), "+f"(d[25]), "+f"(d[26]), "+f"(d[27]), "+f"(d[28]), "+f"(d[29]), "+f"(d[30]), "+f"(d[31]),
          "+f"(d[32]), "+f"(d[33]), "+f"(d[34]), "+f"(d[35]), "+f"(d[36]), "+f"(d[37]), "+f"(d[38]), "+f"(d[39]),
          "+f"(d[40]), "+f"(d[41]), "+f"(d[42]), "+f"(d[43]), "+f"(d[44]), "+f"(d[45]), "+f"(d[46]), "+f"(d[47]),
          "+f"(d[48]), "+f"(d[49]), "+f"(d[50]), "+f"(d[51]), "+f"(d[52]), "+f"(d[53]), "+f"(d[54]), "+f"(d[55]),
          "+f"(d[56]), "+f"(d[57]), "+f"(d[58]), "+f"(d[59]), "+f"(d[60]), "+f"(d[61]), "+f"(d[62]), "+f"(d[63])
        : "r"(a.x), "r"(a.y), "r"(a.z), "r"(a.w), "r"(descB));
}

__device__ __forceinline__ void wgmma_rs(float (&d)[32], const uint4& a, uint32_t descB) {
    asm volatile(
        "{\n.reg .pred p;\n.reg .b64 db;\nsetp.eq.b32 p, 0, 0;\n"
        "mov.b64 db, {%36, 0x10};\n"
        "wgmma.mma_async.sync.aligned.m64n64k16.f32.bf16.bf16 "
        "{%0, %1, %2, %3, %4, %5, %6, %7, %8, %9, %10, %11, %12, %13, %14, %15, "
        "%16, %17, %18, %19, %20, %21, %22, %23, %24, %25, %26, %27, %28, %29, %30, %31}, "
        "{%32, %33, %34, %35}, db, p, 1, 1, 1;\n}\n"
        : "+f"(d[0]), "+f"(d[1]), "+f"(d[2]), "+f"(d[3]), "+f"(d[4]), "+f"(d[5]), "+f"(d[6]), "+f"(d[7]),
          "+f"(d[8]), "+f"(d[9]), "+f"(d[10]), "+f"(d[11]), "+f"(d[12]), "+f"(d[13]), "+f"(d[14]), "+f"(d[15]),
          "+f"(d[16]), "+f"(d[17]), "+f"(d[18]), "+f"(d[19]), "+f"(d[20]), "+f"(d[21]), "+f"(d[22]), "+f"(d[23]),
          "+f"(d[24]), "+f"(d[25]), "+f"(d[26]), "+f"(d[27]), "+f"(d[28]), "+f"(d[29]), "+f"(d[30]), "+f"(d[31])
        : "r"(a.x), "r"(a.y), "r"(a.z), "r"(a.w), "r"(descB));
}

__device__ __forceinline__ void wgmma_rs(float (&d)[16], const uint4& a, uint32_t descB) {
    asm volatile(
        "{\n.reg .pred p;\n.reg .b64 db;\nsetp.eq.b32 p, 0, 0;\n"
        "mov.b64 db, {%20, 0x10};\n"
        "wgmma.mma_async.sync.aligned.m64n32k16.f32.bf16.bf16 "
        "{%0, %1, %2, %3, %4, %5, %6, %7, %8, %9, %10, %11, %12, %13, %14, %15}, "
        "{%16, %17, %18, %19}, db, p, 1, 1, 1;\n}\n"
        : "+f"(d[0]), "+f"(d[1]), "+f"(d[2]), "+f"(d[3]), "+f"(d[4]), "+f"(d[5]), "+f"(d[6]), "+f"(d[7]),
          "+f"(d[8]), "+f"(d[9]), "+f"(d[10]), "+f"(d[11]), "+f"(d[12]), "+f"(d[13]), "+f"(d[14]), "+f"(d[15])
        : "r"(a.x), "r"(a.y), "r"(a.z), "r"(a.w), "r"(descB));
}

constexpr int NT = N_ / BN, MT = M_ / BM;
constexpr int W_BYTES = BN * BK * 2;
constexpr int SLAB = 8 * BN * 4;
constexpr int SC_ROW = BN * 2;
constexpr int X_OFF = 0;
constexpr int W_OFF = 10 * 8192;
constexpr int R_OFF = W_OFF + 4 * W_BYTES;
constexpr int SC_OFF = R_OFF + W_BYTES - 2 * SC_ROW;
constexpr int RAW0_OFF = W_OFF + 2 * W_BYTES;
constexpr int BAR_OFF = SC_OFF + 16 * SC_ROW;
constexpr int SMEM_BYTES = BAR_OFF + 896;
constexpr unsigned READY = MT * 7;
constexpr int UM = 22;
constexpr int NAG = 7;

__device__ __align__(1024) uint8_t g_wimg[(size_t)NT * KC * W_BYTES];
__device__ __align__(128) unsigned g_flag[NT * 32];

__host__ __device__ constexpr int slab_at(int u) { return u == 0 ? 2 : u == 1 ? 3 : u == 3 ? 4 : u == 5 ? 5 : (u >= 7 && u <= 16) ? u - 1 : -1; }
__host__ __device__ constexpr int wload_at(int u) {
    return u <= 10 ? ((u & 1) ? -1 : u / 2 + 1) : u <= 17 ? ((u & 1) ? (u + 3) / 2 : -1) : u == 18 ? 11 : u == 19 ? 12 : u == 20 ? 15 : u == 21 ? 13 : -1;
}
__host__ __device__ constexpr int tail_chunk(int j) { return j == 3 ? 15 : j == 4 ? 14 : 11 + j; }
__host__ __device__ constexpr int wbuf(int c) { return c == 15 ? 4 : c & 3; }

template <int NR>
__device__ __forceinline__ void store_cols(const float (&acc)[NR], uint8_t* p) {
#pragma unroll
    for (int j = 0; j < NR / 16; j++) {
        const int i = 16 * j;
        stg128(p + j * 64, pack_bf16(acc[i], acc[i + 1]), pack_bf16(acc[i + 4], acc[i + 5]), pack_bf16(acc[i + 8], acc[i + 9]), pack_bf16(acc[i + 12], acc[i + 13]));
        stg128(p + j * 64 + 8 * N_ * 2, pack_bf16(acc[i + 2], acc[i + 3]), pack_bf16(acc[i + 6], acc[i + 7]), pack_bf16(acc[i + 10], acc[i + 11]), pack_bf16(acc[i + 14], acc[i + 15]));
    }
}

__global__ void __cluster_dims__(2, 1, 1) __launch_bounds__(256, 1)
nf4_gemm_kernel(const uint8_t* __restrict__ qw, const __nv_bfloat16* __restrict__ cb, const __nv_bfloat16* __restrict__ absmax,
                uint8_t* __restrict__ wimg, unsigned* __restrict__ gflags, uint8_t* __restrict__ out, const unsigned zero,
                const __grid_constant__ CUtensorMap tmx, const __grid_constant__ CUtensorMap tmx64, const __grid_constant__ CUtensorMap tmq16,
                const __grid_constant__ CUtensorMap tmq8, const __grid_constant__ CUtensorMap tmq1, const __grid_constant__ CUtensorMap tms) {
    extern __shared__ __align__(1024) uint8_t smem[];
    const int rank = blockIdx.x & 1;
    const int mt = (blockIdx.x & 3) + (blockIdx.x >> 6) * 4, nt = (blockIdx.x >> 2) & 15;
    const uint8_t* share;
    uint4 s1a, s1b;
    asm volatile(
        "{\n.reg .b32 t, b, o, h;\n.reg .b64 a;\n.reg .pred p;\n"
        "mov.u32 t, %%tid.x;\nmov.u32 b, %%ctaid.x;\n"
        "shl.b32 o, t, 4;\nshr.u32 h, t, 3;\nmad.lo.u32 o, h, %10 - 128, o;\n"
        "shr.u32 h, t, 5;\nmad.lo.u32 o, h, 128 - 4 * %10, o;\n"
        "and.b32 h, b, 3;\nmad.lo.u32 o, h, 8 * %10 - %11 / 4, o;\n"
        "shr.u32 h, b, 6;\nmad.lo.u32 o, h, 32 * %10 - 16 * %11, o;\n"
        "mad.lo.u32 o, b, %11 / 4, o;\n"
        "cvt.u64.u32 a, o;\nadd.u64 a, a, %9;\n"
        "ld.global.L1::no_allocate.v4.u32 {%1, %2, %3, %4}, [a + 64 * %10];\n"
        "ld.global.L1::no_allocate.v4.u32 {%5, %6, %7, %8}, [a + 68 * %10];\n"
        "setp.lt.u32 p, b, 64;\n@p prefetch.global.L2 [a + 96 * %10];\n@p prefetch.global.L2 [a + 100 * %10];\n"
        "mov.b64 %0, a;\n}\n"
        : "=l"(share), "=r"(s1a.x), "=r"(s1a.y), "=r"(s1a.z), "=r"(s1a.w), "=r"(s1b.x), "=r"(s1b.y), "=r"(s1b.z), "=r"(s1b.w)
        : "l"(qw), "n"(N_ * 4), "n"(BN * 4) : "memory");
    const uint32_t sbase = smem_u32(smem);
    const int warp = __shfl_sync(~0u, (int)(threadIdx.x >> 5), 0);
    const int wg = warp >> 2, wj = warp & 3;
    const int lane = threadIdx.x & 31;
    const uint32_t bars = sbase + BAR_OFF;
    const uint32_t snap = bars;
    const uint32_t xfull = bars + 64 + wg * 40;
    const uint32_t wfull = bars + 144;
    const uint32_t wempty = bars + 184;
    const uint32_t ringfull = bars + 216;
    const uint32_t rawbar = bars + 248;
    const uint32_t wown = bars + 264;
    const uint32_t stored = bars + 272 - 8;
    const uint32_t wlast = bars + 344;
    const uint32_t xbase = sbase + X_OFF + wg * 40960, wbase = sbase + W_OFF, rbase = sbase + R_OFF;
    const int xrow = mt * BM + wg * 128 + wj * 16;
    const uint8_t* wsrc = wimg + (size_t)nt * KC * W_BYTES;
    unsigned* flags = gflags + nt * 32;

    auto load_x = [&](int u, int cs = -1) {
        const int c = u < UM ? u >> 1 : tail_chunk((u - UM) % 5), b = u < UM ? u & 1 : (u - UM) / 5;
        mbar_expect_tx(xfull + 8 * (u % 5), cs >= 0 ? 3072 : 2048);
        tma_load_2d(xbase + (u % 5) * 8192 + wj * 2048, &tmx, c * BK, xrow + b * 64, xfull + 8 * (u % 5));
        if (cs >= 0) tma_load_2d(rbase + (cs & 3) * SLAB + warp * 1024, &tmq1, nt * BN + warp * 32, cs * BK + mt * 8, xfull + 8 * (u % 5));
    };
    auto load_x64 = [&](int g, int u) {
        const uint32_t bar = bars + 64 + g * 40 + 8 * u;
        mbar_arrive_n(bar, 3);
        mbar_expect_tx(bar, 8192);
        tma_load_2d(sbase + X_OFF + g * 40960 + u * 8192, &tmx64, (u >> 1) * BK, mt * BM + g * 128 + (u & 1) * 64, bar);
    };
    auto load_slab = [&](int c, uint32_t extra = 0) {
        mbar_expect_tx(ringfull + 8 * (c & 3), SLAB + extra);
        tma_load_3d(rbase + (c & 3) * SLAB, &tmq8, 0, c * BK + mt * 8, nt * 7, ringfull + 8 * (c & 3));
    };
    auto load_raw = [&](int p) {
        mbar_expect_tx(rawbar + 8 * p, 2 * SLAB);
        tma_load_3d(sbase + RAW0_OFF + p * 2 * SLAB, &tmq16, 0, rank * 32 + p * 16, nt * 7, rawbar + 8 * p);
    };
    if (warp == 7) {
        if (elect()) {
            mbar_init(rawbar, 1);
            load_raw(0);
        }
        __syncwarp();
        if (elect()) {
            mbar_init(rawbar + 8, 1);
            load_raw(1);
            mbar_init(bars + 64, 4); mbar_init(bars + 72, 4); mbar_init(bars + 104, 4); mbar_init(bars + 112, 4); mbar_init(ringfull + 16, 1);
            mbar_init_fence();
        }
        __syncwarp();
    }
    uint4 c0, c1;
    asm volatile("ld.global.nc.v4.u32 {%0, %1, %2, %3}, [%8];\nld.global.nc.v4.u32 {%4, %5, %6, %7}, [%8 + 16];"
                 : "=r"(c0.x), "=r"(c0.y), "=r"(c0.z), "=r"(c0.w), "=r"(c1.x), "=r"(c1.y), "=r"(c1.z), "=r"(c1.w) : "l"(cb));
    uint2 sc1;
    asm volatile("ld.global.nc.v2.u32 {%0, %1}, [%2];" : "=r"(sc1.x), "=r"(sc1.y) : "l"(absmax + N_ + nt * BN + (warp < 7 ? warp * 32 : 0) + (lane & 7) * 4));
    uint4 sc0;
    asm volatile("ld.global.nc.v4.u32 {%0, %1, %2, %3}, [%4];" : "=r"(sc0.x), "=r"(sc0.y), "=r"(sc0.z), "=r"(sc0.w) : "l"(absmax + nt * BN + (warp < 7 ? warp * 32 : 0) + (lane >> 3) * 8));
    if (warp < 7) {
        delay(200);
        const uint8_t* p0 = share + (lane & 1) * (4 * N_ * 4);
        asm volatile("prefetch.global.L2 [%0];" ::"l"(p0));
        if (blockIdx.x < 64) asm volatile("prefetch.global.L2 [%0];" ::"l"(p0 + 32 * N_ * 4));
    }
    if (warp == 5 || warp == 6) {
        if (elect()) {
            if (warp == 6) {
#pragma unroll
                for (int s = 0; s < 5; s++) mbar_init(wfull + 8 * s, 1);
#pragma unroll
                for (int s = 0; s < 4; s++) mbar_init(wempty + 8 * s, 16);
                mbar_init(wown, 7); mbar_init(wlast, 1); mbar_init(ringfull, 1); mbar_init(ringfull + 24, 1);
                mbar_expect_tx(wfull, W_BYTES / 2);
            }
            if (warp == 5) {
#pragma unroll
                for (int s = 0; s < 10; s++) if (s % 5 >= 2) mbar_init(bars + 64 + 8 * s, 4);
#pragma unroll
                for (int s = 1; s <= NAG; s++) mbar_init(stored + 8 * s, s == 1 ? 7 : 224);
            }
            mbar_init_fence();
        }
        __syncwarp();
    }
    cluster_arrive();
    if (warp == 7) {
        if (elect()) { load_x64(0, 0); load_x64(0, 1); load_x64(1, 0); load_x64(1, 1); }
        __syncwarp();
    }
    const uint32_t rlane = (lane & 7) * 128 + ((((lane >> 3) * 2) ^ (lane & 7)) << 4);
    const uint32_t wlane = warp * 1024 + (lane & 7) * 16 + (lane >> 3) * 4;
    const uint32_t slabsrc = __shfl_sync(~0u, (warp < 7 ? warp * 1024 + rlane : 0) + sbase, lane);
    const uint32_t scsrc = __shfl_sync(~0u, sbase + (warp < 7 ? warp * 64 : 0) + (lane >> 3) * 16, lane);
    uint8_t* const gdst = wimg + (size_t)nt * KC * W_BYTES + (mt >> 1) * SLAB + (mt & 1) * 128 + wlane;
    uint8_t* const gkeep = (uint8_t*)__shfl_sync(~0u, (unsigned long long)gdst, lane);
    uint8_t* const gread = (uint8_t*)__shfl_sync(~0u, (unsigned long long)(warp < 7 ? gdst + (lane >> 3) * 252 : (uint8_t*)flags + (lane >> 3) * 16), lane);
    Lut lut = {};
    if (warp < 7) {
        lut.lo[0] = __byte_perm(c0.x, c0.y, 0x6420); lut.hi[0] = __byte_perm(c0.x, c0.y, 0x7531);
        lut.lo[1] = __byte_perm(c0.z, c0.w, 0x6420); lut.hi[1] = __byte_perm(c0.z, c0.w, 0x7531);
        lut.lo[2] = __byte_perm(c1.x, c1.y, 0x6420); lut.hi[2] = __byte_perm(c1.x, c1.y, 0x7531);
        lut.lo[3] = __byte_perm(c1.z, c1.w, 0x6420); lut.hi[3] = __byte_perm(c1.z, c1.w, 0x7531);
    }
    cluster_wait();

    auto store_slab = [&](int c, uint32_t p, const uint4& sc) {
        const uint4 w = dequant8(p, sc, lut);
        uint8_t* g = gkeep + (size_t)c * W_BYTES;
        stg32(g, w.x); stg32(g + 256, w.y); stg32(g + 512, w.z); stg32(g + 768, w.w);
        read_l2(scsrc + SC_OFF + SC_ROW * c, gread + (size_t)c * W_BYTES, (lane & 7) == 0);
        if (c <= NAG) read_arrive(stored + 8 * c);
    };
    auto take_sample = [&]() { read_l2(scsrc + BAR_OFF, gread, (lane & 7) == 0); };
    auto load_w = [&](int c) {
        read_wait<0>();
        poll_ge(flags + c, lds32(snap + 4 * c), READY);
        asm volatile("fence.acquire.gpu;" ::: "memory");
        asm volatile("fence.proxy.async.global;" ::: "memory");
        if (c >= 4 && c < 15) mbar_wait(wempty + 8 * (c & 3), ((c >> 2) - 1) & 1);
        if (elect()) {
            if (c == 1) {
                mbar_expect_tx(wfull + 8, W_BYTES / 2);
                bulk_load_mc(wbase + W_BYTES + rank * SLAB, wsrc + W_BYTES + rank * SLAB, SLAB, wfull + 8);
                mbar_expect_tx(wlast, W_BYTES / 2);
                bulk_load_mc(wbase + W_BYTES + (2 + rank) * SLAB, wsrc + W_BYTES + (2 + rank) * SLAB, SLAB, wlast);
            } else {
                mbar_expect_tx(wfull + 8 * wbuf(c), W_BYTES);
                bulk_load_mc(wbase + wbuf(c) * W_BYTES + rank * (W_BYTES / 2), wsrc + (size_t)c * W_BYTES + rank * (W_BYTES / 2), W_BYTES / 2, wfull + 8 * wbuf(c));
            }
        }
        __syncwarp();
    };

    if (warp < 7) {
        {
            const uint4 w = dequant8(pack8(s1a, s1b), make_uint4(sc1.x, sc1.y, sc1.x, sc1.y), lut);
            uint8_t* g = wimg + (size_t)(nt * KC + 1) * W_BYTES + (mt >> 1) * SLAB + (mt & 1) * 128
                       + warp * 1024 + (lane & 1) * 512 + (lane >> 3) * 16 + ((lane & 7) >> 1) * 4;
            stg32(g, w.x); stg32(g + 64, w.z); stg32(g + 256, w.y); stg32(g + 320, w.w);
            __syncwarp();
            if (elect()) mbar_arrive(stored + 8);
            __syncwarp();
        }
        const uint32_t tab = prmt(prmt(lane & 8 ? lut.lo[2] : lut.lo[0], lane & 8 ? lut.lo[3] : lut.lo[1], lane & 7),
                                  prmt(lane & 8 ? lut.hi[2] : lut.hi[0], lane & 8 ? lut.hi[3] : lut.hi[1], lane & 7), 0x40);
#pragma unroll
        for (int p = 0; p < 2; p++) {
            mbar_wait(rawbar + 8 * p, 0);
            const uint32_t a = sbase + RAW0_OFF + p * 2 * SLAB + warp * 2048;
            const uint4 v0 = lds128(a + rlane), v1 = lds128(a + (rlane ^ 16)), v2 = lds128(a + rlane + 1024), v3 = lds128(a + (rlane ^ 16) + 1024);
            const uint4 w0 = dequant8(pack8(v0, v1), sc0, lut), w1 = dequant8_shfl(v2, v3, sc0, tab);
            const uint32_t d = wbase + (2 * rank + p) * SLAB, e = d + wlane;
            sts32(e, w0.x); sts32(e + 256, w0.y); sts32(e + 512, w0.z); sts32(e + 768, w0.w);
            sts32(e + 128, w1.x); sts32(e + 384, w1.y); sts32(e + 640, w1.z); sts32(e + 896, w1.w);
            fence_async_smem();
            __syncwarp();
            if (elect()) {
                if (p == 1) mbar_arrive(wown);
                copy_to_peer(d + warp * 1024, 1024, wfull, rank ^ 1);
            }
            __syncwarp();
        }
    } else {
        mbar_wait(stored + 8, 0);
        const uint8_t* g1 = wsrc + W_BYTES + (mt >> 1) * SLAB + (mt & 1) * 128 + (lane >> 1) * 256 + (lane & 1) * 64;
        const unsigned v0 = ld_relaxed(g1), v1 = ld_relaxed(g1 + 3072);
        if (elect()) {
            load_slab(2, 14 * SC_ROW);
            tma_load_2d(sbase + SC_OFF + 2 * SC_ROW, &tms, nt * BN, 2, ringfull + 16);
        }
        __syncwarp();
        const unsigned n = after(after(7, v0, zero), v1, zero);
        __syncwarp();
        if (elect()) red_add(flags + 1, n);
        __syncwarp();
        if (elect()) load_slab(3);
        __syncwarp();
        mbar_wait(wown, 0);
        if (elect()) { load_x64(0, 2); load_x64(0, 3); load_x64(1, 2); load_x64(1, 3); }
        __syncwarp();
    }

    float acc0[112], acc1[112];
    const uint32_t descA = ((xbase & 0x3FFFF) >> 4) | (1u << 16), descB = ((wbase & 0x3FFFF) >> 4) | ((128u >> 4) << 16);
    static_for<0, UM>([&](auto U) __attribute__((always_inline)) {
        constexpr int u = U.value, kc = u >> 1;
        constexpr int c = slab_at(u);
        uint32_t da = descA, db = descB;
        asm volatile("" : "+r"(da), "+r"(db));
        uint4 q0, q1, sc;
        auto slab_loads = [&]() {
            q0 = lds128(slabsrc + R_OFF + (c & 3) * SLAB); q1 = lds128((slabsrc ^ 16) + R_OFF + (c & 3) * SLAB);
            sc = lds128(scsrc + SC_OFF + SC_ROW * (c & 15));
        };
        if (u < 4) {
            if (u == 0) mbar_wait3(xfull, 0, xfull + 8, 0, wown, 0);
            if (u == 1) mbar_wait(wfull, 0);
            if (u == 2) mbar_wait3(xfull + 16, 0, xfull + 24, 0, wfull + 8, 0);
            if (u == 3) { mbar_wait2(wlast, 0, ringfull, 0); slab_loads(); }
            if (u == 0 && warp == 7) take_sample();
            const int h = u < 2 ? rank ^ u : u & 1;
            da += kc * 1024 + h * 4; db += kc * (W_BYTES >> 4) + h * (2 * SLAB >> 4);
            wgmma_fence();
            wgmma_ss<u != 0>(acc0, da, db); wgmma_ss<u != 0>(acc1, da + 512, db);
            wgmma_ss<1>(acc0, da + 2, db + (SLAB >> 4)); wgmma_ss<1>(acc1, da + 514, db + (SLAB >> 4));
        } else {
            if (u & 1) mbar_wait(xfull + 8 * (u % 5), (u / 5) & 1);
            else mbar_wait2(xfull + 8 * (u % 5), (u / 5) & 1, wfull + 8 * (kc & 3), (kc >> 2) & 1);
            if (c >= 0) slab_loads();
            da += (u % 5) * 512; db += (kc & 3) * (W_BYTES >> 4);
            wgmma_fence();
#pragma unroll
            for (int ks = 0; ks < 4; ks++) {
                if (u & 1) wgmma_ss<1>(acc1, da + ks * 2, db + ks * (SLAB >> 4));
                else wgmma_ss<1>(acc0, da + ks * 2, db + ks * (SLAB >> 4));
            }
        }
        wgmma_commit();
        if (u >= 2) wgmma_wait<1>();
        if (warp < 7) {
            constexpr int cp = slab_at(u - 2) > NAG ? slab_at(u - 2) : -1;
            if constexpr (u < 2) { mbar_wait(ringfull + 8 * c, 0); slab_loads(); }
            uint32_t p = 0;
            if (c >= 0) p = pack8(q0, q1);
            if (cp >= 0) { if (slab_at(u - 1) >= 0) read_wait<1>(); else read_wait<0>(); }
            if (u >= 2) {
                if (elect()) {
                    if (u <= 17) load_x(u + 3, slab_at(u + 3));
                    if (u >= 17) load_x(u + 4);
                    if (!(u & 1)) mbar_arrive_both(wempty + 8 * ((kc - 1) & 3));
                    if (cp >= 0) red_add(flags + cp, 1);
                }
                __syncwarp();
            }
            if (c >= 0) store_slab(c, p, sc);
        } else {
            constexpr int cw = wload_at(u), cc = slab_at(u - 1) <= NAG ? slab_at(u - 1) : -1;
            if (cw >= 0 && cw <= 6) load_w(cw);
            if (u != 1) {
                if (elect()) {
                    if (u == 0) load_slab(4);
                    if (u >= 2 && u <= 17) load_x(u + 3);
                    if (u >= 17) load_x(u + 4);
                    if (u >= 2 && !(u & 1)) mbar_arrive_both(wempty + 8 * ((kc - 1) & 3));
                }
                __syncwarp();
            }
            if constexpr (cc >= 0) {
                mbar_wait(stored + 8 * cc, 0);
                if (elect()) red_add(flags + cc, 7);
                __syncwarp();
            }
            if (u == 1) {
                if (elect()) { load_x64(0, 4); load_x64(1, 4); }
                __syncwarp();
                delay(300);
            }
            if (cw > 6) load_w(cw);
            if (wload_at(u + 1) >= 0) take_sample();
        }
    });

    uint32_t tA = descA, tB = descB;
    asm volatile("" : "+r"(tA), "+r"(tB));
    if (wg == 1) {
        wgmma_wait<0>();
        if (elect()) { load_x(UM + 4); mbar_arrive_both(wempty + 16); }
        __syncwarp();
        if (warp == 7) load_w(14);
        if (warp == 7 && lane == 0) {
            if (atomicAdd(flags + 16, 1) == MT - 1) {
#pragma unroll
                for (int c = 0; c <= 16; c++) flags[c] = 0;
            }
        }
        __syncwarp();
        bar_sync<256>(1);
    }
#pragma unroll
    for (int j = 0; j < 5; j++) {
        const int c = tail_chunk(j), v = UM + j;
        mbar_wait2(xfull + 8 * (v % 5), (v / 5) & 1, wfull + 8 * wbuf(c), c == 15 ? 0 : (c >> 2) & 1);
        wgmma_fence();
#pragma unroll
        for (int ks = 0; ks < 4; ks++) wgmma_ss<1>(acc0, tA + (v % 5) * 512 + ks * 2, tB + wbuf(c) * (W_BYTES >> 4) + ks * (SLAB >> 4));
        wgmma_commit();
        if (j == 4) bar_arrive<256>(1 + wg);
        if (j == 0) {
            if (wg == 0) {
                wgmma_wait<1>();
                if (elect()) { load_x(UM + 4); mbar_arrive_both(wempty + 16); }
                __syncwarp();
            }
        } else if (j >= 2) {
            wgmma_wait<2>();
            if (elect()) load_x(v + 3);
            __syncwarp();
        }
    }
    wgmma_wait<1>();
    if (elect()) load_x(UM + 8);
    __syncwarp();
    uint4 af[20];
    const uint32_t alane = xbase + wj * 2048 + (lane & 15) * 128 + (((lane >> 4) ^ (lane & 7)) << 4);
    auto fragments = [&](int j) {
#pragma unroll
        for (int ks = 0; ks < 4; ks++) af[4 * j + ks] = ldmatrix_x4((alane ^ (ks * 32)) + ((UM + 5 + j) % 5) * 8192);
    };
    mbar_wait(xfull + 8 * ((UM + 5) % 5), ((UM + 5) / 5) & 1);
    fragments(0);
    wgmma_wait<0>();
    if (elect()) load_x(UM + 9);
    __syncwarp();
    uint8_t* optr = out + (size_t)(xrow + (lane >> 2)) * (N_ * 2) + nt * (BN * 2) + (lane & 3) * 16;
    float pa[64], pb[32], pc[16];
#pragma unroll
    for (int i = 0; i < 64; i++) asm volatile("mov.b32 %0, %1;" : "=f"(pa[i]) : "f"(acc1[i]));
#pragma unroll
    for (int i = 0; i < 32; i++) asm volatile("mov.b32 %0, %1;" : "=f"(pb[i]) : "f"(acc1[64 + i]));
#pragma unroll
    for (int i = 0; i < 16; i++) asm volatile("mov.b32 %0, %1;" : "=f"(pc[i]) : "f"(acc1[96 + i]));
    uint32_t pk[56];
    auto store_pk = [&](int h0, int h1) {
#pragma unroll
        for (int h = h0; h < h1; h++) {
            const int i = 8 * (h >> 1) + (h & 1);
            stg128(optr + (h >> 1) * 64 + (h & 1) * (8 * N_ * 2), pk[i], pk[i + 2], pk[i + 4], pk[i + 6]);
        }
    };
    static_for<0, 4>([&](auto J) __attribute__((always_inline)) {
        constexpr int j = J.value, v = UM + 5 + j;
        if (j > 0) { mbar_wait(xfull + 8 * (v % 5), (v / 5) & 1); fragments(j); }
#pragma unroll
        for (int i = 16 * j; i < (j < 3 ? 16 * j + 16 : 56); i++) pk[i] = pack_bf16(acc0[2 * i], acc0[2 * i + 1]);
        store_pk(2 * j, 2 * j + 2);
        if (j == 1) {
#pragma unroll
            for (int ks = 0; ks < 4; ks++) af[ks] = make_uint4(after(af[ks].x, zero, zero), after(af[ks].y, zero, zero), after(af[ks].z, zero, zero), after(af[ks].w, zero, zero));
        }
    });
    store_pk(8, 10);
    if (wg == 0) store_pk(10, 14);
    auto piece = [&](auto& d, auto CB) {
        constexpr int cb = CB.value;
        wgmma_fence();
#pragma unroll
        for (int j = 0; j < 5; j++) {
            if (cb == 0 && j == 4) { mbar_wait(xfull + 8 * ((UM + 9) % 5), ((UM + 9) / 5) & 1); wgmma_fence(); }
#pragma unroll
            for (int ks = 0; ks < 4; ks++) {
                const uint32_t db = tB + wbuf(tail_chunk(j)) * (W_BYTES >> 4) + ks * (SLAB >> 4) + cb * 64;
                if (j < 4 || cb > 0) wgmma_rs(d, af[4 * j + ks], db);
                else if constexpr (cb == 0) wgmma_ss<1>(d, tA + ((UM + 9) % 5) * 512 + ks * 2, db);
            }
        }
        wgmma_commit();
    };
    bar_sync<256>(2 + wg);
    piece(pa, IC<0>{});
    bar_arrive<256>(3 + wg);
    if (wg == 1) store_pk(10, 14);
    wgmma_wait<0>();
    fragments(4);
    optr += 64 * N_ * 2;
    store_cols(pa, optr);
    bar_sync<256>(4 + wg);
    piece(pb, IC<4>{});
    bar_arrive<256>(5 + wg);
    wgmma_wait<0>();
    store_cols(pb, optr + 4 * 64);
    bar_sync<256>(6 + wg);
    piece(pc, IC<6>{});
    if (wg == 0) bar_arrive<256>(7);
    cluster_arrive();
    wgmma_wait<0>();
    store_cols(pc, optr + 6 * 64);
    cluster_wait();
}

typedef CUresult (*EncodeFn)(CUtensorMap*, CUtensorMapDataType, cuuint32_t, void*, const cuuint64_t*, const cuuint64_t*,
                             const cuuint32_t*, const cuuint32_t*, CUtensorMapInterleave, CUtensorMapSwizzle,
                             CUtensorMapL2promotion, CUtensorMapFloatOOBfill);

extern "C" void kernel_launch(void* const* d_in, const int* in_sizes, int n_in, void* d_out, int out_size) {
    static EncodeFn encode = nullptr;
    static void *wimg = nullptr, *gflags = nullptr;
    if (!encode) {
        cudaGetSymbolAddress(&wimg, g_wimg);
        cudaGetSymbolAddress(&gflags, g_flag);
        void* fn = nullptr;
        cudaDriverEntryPointQueryResult qr;
        cudaGetDriverEntryPoint("cuTensorMapEncodeTiled", &fn, cudaEnableDefault, &qr);
        encode = (EncodeFn)fn;
        cudaFuncSetAttribute(nf4_gemm_kernel, cudaFuncAttributeMaxDynamicSharedMemorySize, SMEM_BYTES);
    }
    void *x = d_in[0], *qw = d_in[1], *cb = d_in[2], *absmax = d_in[3];
    auto map = [&](CUtensorMapDataType t, int rank, void* p, const cuuint64_t* dims, const cuuint64_t* strides, const cuuint32_t* box, bool swizzle) {
        CUtensorMap m;
        const cuuint32_t es[3] = {1, 1, 1};
        encode(&m, t, rank, p, dims, strides, box, es, CU_TENSOR_MAP_INTERLEAVE_NONE,
               swizzle ? CU_TENSOR_MAP_SWIZZLE_128B : CU_TENSOR_MAP_SWIZZLE_NONE,
               swizzle ? CU_TENSOR_MAP_L2_PROMOTION_L2_128B : CU_TENSOR_MAP_L2_PROMOTION_NONE, CU_TENSOR_MAP_FLOAT_OOB_FILL_NONE);
        return m;
    };
    const cuuint64_t xd[2] = {K_, M_}, xs[1] = {K_ * 2};
    const cuuint64_t q3d[3] = {32, K_, N_ / 32}, q3s[2] = {N_ * 4, 128};
    const cuuint64_t q2d[2] = {N_, K_}, q2s[1] = {N_ * 4};
    const cuuint64_t sd[2] = {N_, KC}, ss[1] = {N_ * 2};
    const cuuint32_t bx[2] = {BK, 16}, bx64[2] = {BK, 64}, bq16[3] = {32, 16, 7}, bq8[3] = {32, 8, 7}, bq1[2] = {32, 8}, bs[2] = {BN, KC - 2};
    nf4_gemm_kernel<<<128, 256, SMEM_BYTES>>>(
        (const uint8_t*)qw, (const __nv_bfloat16*)cb, (const __nv_bfloat16*)absmax, (uint8_t*)wimg, (unsigned*)gflags, (uint8_t*)d_out, 0u,
        map(CU_TENSOR_MAP_DATA_TYPE_BFLOAT16, 2, x, xd, xs, bx, true), map(CU_TENSOR_MAP_DATA_TYPE_BFLOAT16, 2, x, xd, xs, bx64, true),
        map(CU_TENSOR_MAP_DATA_TYPE_INT32, 3, qw, q3d, q3s, bq16, true), map(CU_TENSOR_MAP_DATA_TYPE_INT32, 3, qw, q3d, q3s, bq8, true),
        map(CU_TENSOR_MAP_DATA_TYPE_INT32, 2, qw, q2d, q2s, bq1, true), map(CU_TENSOR_MAP_DATA_TYPE_BFLOAT16, 2, absmax, sd, ss, bs, false));
}
```
